```python
import torch

def _softmax(x, axis=-1):
    return torch.softmax(x, dim=axis)
def _gelu(x):
    return torch.nn.functional.gelu(x, approximate="tanh")
def _silu(x):
    return torch.nn.functional.silu(x)
def _sigmoid(x):
    return torch.sigmoid(x)
def _layernorm(x, axis=-1, eps=1e-5):
    m = x.mean(dim=axis, keepdim=True)
    v = x.var(dim=axis, keepdim=True, unbiased=False)
    return (x - m) / torch.sqrt(v + eps)
def _scatter_add(tgt, idx, src, axis=0):
    return tgt.clone().index_add_(axis, idx, src)
def _segment_sum(src, seg, n):
    out = torch.zeros((n,) + src.shape[1:], dtype=src.dtype)
    return out.index_add_(0, seg, src)
def _pad(x, pw):
    flat = tuple(v for pair in reversed(pw) for v in pair)
    return torch.nn.functional.pad(x, flat)

kernel_name = 'concat_heads__gqa_block_cached__gqa_block_cached__near_ridge'

def setup_inputs():

    _w = (lambda a: (lambda t: t.to(torch.bfloat16) if t.is_floating_point() else t)(torch.as_tensor(a)))
    def _A_setup():
        B, Sq, D = 8, 64, 512
        Hq, Hkv, Sk, Dh = 32, 8, 2048, 128
        assert Hq % Hkv == 0, (Hq, Hkv)
        return {
            "x": _w((lambda *s: torch.randn(*s, dtype=torch.bfloat16) * 0.8)(B, Sq, D)),
            "k_cache": _w((lambda *s: torch.randn(*s, dtype=torch.bfloat16) * 0.8)(B, Hkv, Sk, Dh)),
            "v_cache": _w((lambda *s: torch.randn(*s, dtype=torch.bfloat16) * 0.05)(B, Hkv, Sk, Dh)),
            "wq": _w((lambda *s: torch.randn(*s, dtype=torch.bfloat16) * 0.8)(D, Hq * Dh) * (D ** -0.5)),
            "wo": _w((lambda *s: torch.randn(*s, dtype=torch.bfloat16) * 0.05)(Hq * Dh, D) * ((Hq * Dh) ** -0.5)),
        }
    _A_in = _A_setup()

    def _B_setup():
        B, Sq, D = 8, 64, 512
        Hq, Hkv, Sk, Dh = 32, 8, 2048, 128
        assert Hq % Hkv == 0, (Hq, Hkv)
        return {
            "x": _w((lambda *s: torch.randn(*s, dtype=torch.bfloat16) * 0.8)(B, Sq, D)),
            "k_cache": _w((lambda *s: torch.randn(*s, dtype=torch.bfloat16) * 0.8)(B, Hkv, Sk, Dh)),
            "v_cache": _w((lambda *s: torch.randn(*s, dtype=torch.bfloat16) * 0.05)(B, Hkv, Sk, Dh)),
            "wq": _w((lambda *s: torch.randn(*s, dtype=torch.bfloat16) * 0.8)(D, Hq * Dh) * (D ** -0.5)),
            "wo": _w((lambda *s: torch.randn(*s, dtype=torch.bfloat16) * 0.05)(Hq * Dh, D) * ((Hq * Dh) ** -0.5)),
        }
    _B_in = _B_setup()

    return {
        "A_x": _A_in["x"],
        "A_k_cache": _A_in["k_cache"],
        "A_v_cache": _A_in["v_cache"],
        "A_wq": _A_in["wq"],
        "A_wo": _A_in["wo"],
        "B_x": _B_in["x"],
        "B_k_cache": _B_in["k_cache"],
        "B_v_cache": _B_in["v_cache"],
        "B_wq": _B_in["wq"],
        "B_wo": _B_in["wo"],
    }

def reference(A_x, A_k_cache, A_v_cache, A_wq, A_wo, B_x, B_k_cache, B_v_cache, B_wq, B_wo):
    def _A_ref(x, k_cache, v_cache, wq, wo):
        B, Sq, D = x.shape
        Hq, Dh = 32, 128
        Hkv = k_cache.shape[1]
        rep = Hq // Hkv
        q = (lambda x, *d: x.permute(*d))((x @ wq).reshape(B, Sq, Hq, Dh), 0, 2, 1, 3)
        k = (lambda x, n, axis: torch.repeat_interleave(x, n, dim=axis))(k_cache, rep, axis=1)
        v = (lambda x, n, axis: torch.repeat_interleave(x, n, dim=axis))(v_cache, rep, axis=1)
        scores = torch.einsum("bhqd,bhkd->bhqk", q, k) * (Dh ** -0.5)
        p = _softmax(scores, axis=-1)
        o = torch.einsum("bhqk,bhkd->bhqd", p, v)
        return (lambda x, *d: x.permute(*d))(o, 0, 2, 1, 3).reshape(B, Sq, Hq * Dh) @ wo

    def _B_ref(x, k_cache, v_cache, wq, wo):
        B, Sq, D = x.shape
        Hq, Dh = 32, 128
        Hkv = k_cache.shape[1]
        rep = Hq // Hkv
        q = (lambda x, *d: x.permute(*d))((x @ wq).reshape(B, Sq, Hq, Dh), 0, 2, 1, 3)
        k = (lambda x, n, axis: torch.repeat_interleave(x, n, dim=axis))(k_cache, rep, axis=1)
        v = (lambda x, n, axis: torch.repeat_interleave(x, n, dim=axis))(v_cache, rep, axis=1)
        scores = torch.einsum("bhqd,bhkd->bhqk", q, k) * (Dh ** -0.5)
        p = _softmax(scores, axis=-1)
        o = torch.einsum("bhqk,bhkd->bhqd", p, v)
        return (lambda x, *d: x.permute(*d))(o, 0, 2, 1, 3).reshape(B, Sq, Hq * Dh) @ wo

    a = _A_ref(A_x, A_k_cache, A_v_cache, A_wq, A_wo)
    b = _B_ref(B_x, B_k_cache, B_v_cache, B_wq, B_wo)
    return torch.concatenate([a, b], axis=-1)
```

```cpp
#include <cuda_runtime.h>
#include <cuda.h>
#include <cuda_bf16.h>
#include <stdint.h>

#define SUM_HADD2 0
#define TRACE 0

namespace {

constexpr int UNIT = 32768;
constexpr int SLOT = 2 * UNIT;
constexpr int NSLOT = 3;
constexpr int OFF_STASH = 6 * UNIT;
constexpr int OFF_BAR = 7 * UNIT;
constexpr int SMEM_BYTES = OFF_BAR + 256 + 1024;
constexpr int QSTAGES = 8;
constexpr int NSTEP = 33;
constexpr float SUM_LIMIT = 4096.f;
constexpr int SPIN_LIMIT = 1 << 22;

enum { B_FULL = 0, B_EMPTY = 3, B_WFULL = 6, B_WEMPTY = 10, B_O1_READY = 14, B_U3_FREE = 15, B_U1_FREE = 16,
       B_O1_IN = 17, B_O2_IN = 18, B_O2_OWN0 = 20, B_ZERO_OK = 21, B_COUNT = 22 };
enum { NB_PP0 = 1, NB_WG0 = 3, NB_START0 = 5 };

struct Params {
  CUtensorMap x[2], wq[2], k[2], v[2], wo[2], out;
};

__device__ unsigned int g_zero_cnt[16];

__device__ __forceinline__ uint32_t smem_u32(const void* p) { return (uint32_t)__cvta_generic_to_shared(p); }
__device__ __forceinline__ void mbar_init(uint32_t bar, uint32_t cnt) { asm volatile("mbarrier.init.shared::cta.b64 [%0], %1;" :: "r"(bar), "r"(cnt)); }
__device__ __forceinline__ void mbar_expect_tx(uint32_t bar, uint32_t bytes) { asm volatile("mbarrier.arrive.expect_tx.shared::cta.b64 _, [%0], %1;" :: "r"(bar), "r"(bytes) : "memory"); }
__device__ __forceinline__ void mbar_arrive(uint32_t bar) { asm volatile("mbarrier.arrive.shared::cta.b64 _, [%0];" :: "r"(bar) : "memory"); }
__device__ __forceinline__ uint32_t mapa(uint32_t addr, uint32_t cta) { uint32_t r; asm("mapa.shared::cluster.u32 %0, %1, %2;" : "=r"(r) : "r"(addr), "r"(cta)); return r; }
__device__ __forceinline__ void mbar_arrive_remote(uint32_t rbar) { asm volatile("mbarrier.arrive.release.cluster.shared::cluster.b64 _, [%0];" :: "r"(rbar) : "memory"); }
__device__ __forceinline__ bool mbar_try(uint32_t bar, uint32_t parity) {
  uint32_t ok;
  asm volatile("{ .reg .pred p; mbarrier.try_wait.parity.shared::cta.b64 p, [%1], %2; selp.u32 %0, 1, 0, p; }" : "=r"(ok) : "r"(bar), "r"(parity) : "memory");
  return ok;
}
__device__ __forceinline__ bool mbar_try_cluster(uint32_t bar, uint32_t parity) {
  uint32_t ok;
  asm volatile("{ .reg .pred p; mbarrier.try_wait.parity.acquire.cluster.shared::cta.b64 p, [%1], %2; selp.u32 %0, 1, 0, p; }" : "=r"(ok) : "r"(bar), "r"(parity) : "memory");
  return ok;
}
__device__ __forceinline__ void mbar_wait(uint32_t bar, uint32_t parity) {
  if (mbar_try(bar, parity)) return;
#pragma unroll 1
  for (int i = 0; i < SPIN_LIMIT; i++) if (mbar_try(bar, parity)) return;
  __trap();
}
__device__ __forceinline__ void mbar_wait_sleep(uint32_t bar, uint32_t parity) {
#pragma unroll 1
  for (int i = 0; i < SPIN_LIMIT; i++) { if (mbar_try(bar, parity)) return; __nanosleep(200); }
  __trap();
}
__device__ __forceinline__ void mbar_wait_cluster(uint32_t bar, uint32_t parity) {
#pragma unroll 1
  for (int i = 0; i < SPIN_LIMIT; i++) if (mbar_try_cluster(bar, parity)) return;
  __trap();
}
__device__ __forceinline__ void tma_2d(uint32_t dst, const CUtensorMap* m, int c0, int c1, uint32_t bar) {
  asm volatile("cp.async.bulk.tensor.2d.shared::cluster.global.mbarrier::complete_tx::bytes [%0], [%1, {%3, %4}], [%2];"
    :: "r"(dst), "l"(m), "r"(bar), "r"(c0), "r"(c1) : "memory");
}
__device__ __forceinline__ void tma_3d(uint32_t dst, const CUtensorMap* m, int c1, int c2, uint32_t bar) {
  asm volatile("cp.async.bulk.tensor.3d.shared::cluster.global.mbarrier::complete_tx::bytes [%0], [%1, {%3, %4, %5}], [%2];"
    :: "r"(dst), "l"(m), "r"(bar), "r"(0), "r"(c1), "r"(c2) : "memory");
}
__device__ __forceinline__ void tma_red_3d(const CUtensorMap* m, int c1, int c2, uint32_t src) {
  asm volatile("cp.reduce.async.bulk.tensor.3d.global.shared::cta.add.tile.bulk_group [%0, {%2, %3, %4}], [%1];"
    :: "l"(m), "r"(src), "r"(0), "r"(c1), "r"(c2) : "memory");
}
__device__ __forceinline__ void dsmem_copy(uint32_t rdst, uint32_t src, uint32_t bytes, uint32_t rbar) {
  asm volatile("cp.async.bulk.shared::cluster.shared::cta.mbarrier::complete_tx::bytes [%0], [%1], %2, [%3];"
    :: "r"(rdst), "r"(src), "r"(bytes), "r"(rbar) : "memory");
}
__device__ __forceinline__ void prefetch_map(const CUtensorMap* m) { asm volatile("prefetch.tensormap [%0];" :: "l"(m) : "memory"); }
__device__ __forceinline__ void fence_async_smem() { asm volatile("fence.proxy.async.shared::cta;" ::: "memory"); }
__device__ __forceinline__ void bar_sync(int id, int n) { asm volatile("bar.sync %0, %1;" :: "r"(id), "r"(n) : "memory"); }
__device__ __forceinline__ void bar_arrive(int id, int n) { asm volatile("bar.arrive %0, %1;" :: "r"(id), "r"(n) : "memory"); }
__device__ __forceinline__ void cluster_arrive() { asm volatile("barrier.cluster.arrive.relaxed.aligned;" ::: "memory"); }
__device__ __forceinline__ void cluster_wait() { asm volatile("barrier.cluster.wait.aligned;" ::: "memory"); }
__device__ __forceinline__ void wg_fence() { asm volatile("wgmma.fence.sync.aligned;" ::: "memory"); }
__device__ __forceinline__ void wg_commit() { asm volatile("wgmma.commit_group.sync.aligned;" ::: "memory"); }
template <int N> __device__ __forceinline__ void wg_wait() { asm volatile("wgmma.wait_group.sync.aligned %0;" :: "n"(N) : "memory"); }
template <int N> __device__ __forceinline__ void fence_regs(float (&d)[N]) {
#pragma unroll
  for (int i = 0; i < N; i++) asm volatile("" : "+f"(d[i]) :: "memory");
}
template <int N> __device__ __forceinline__ void fence_regs(uint32_t (&d)[N]) {
#pragma unroll
  for (int i = 0; i < N; i++) asm volatile("" : "+r"(d[i]) :: "memory");
}
__device__ __forceinline__ uint64_t mk_desc(uint32_t lo) { return ((uint64_t)0x40000040u << 32) | lo; }
__device__ __forceinline__ float ex2(float x) { float y; asm("ex2.approx.ftz.f32 %0, %1;" : "=f"(y) : "f"(x)); return y; }
__device__ __forceinline__ uint32_t pack_bf16(float lo, float hi) { uint32_t r; asm("cvt.rn.bf16x2.f32 %0, %1, %2;" : "=r"(r) : "f"(hi), "f"(lo)); return r; }
__device__ __forceinline__ uint32_t hadd2(uint32_t a, uint32_t b) { uint32_t r; asm("add.rn.bf16x2 %0, %1, %2;" : "=r"(r) : "r"(a), "r"(b)); return r; }
__device__ __forceinline__ void stsm4(uint32_t addr, uint32_t a, uint32_t b, uint32_t c, uint32_t d) {
  asm volatile("stmatrix.sync.aligned.m8n8.x4.shared.b16 [%0], {%1, %2, %3, %4};" :: "r"(addr), "r"(a), "r"(b), "r"(c), "r"(d) : "memory");
}
#define TR(who, i) do {} while (0)

template <int TB>
__device__ __forceinline__ void wgmma_ss_n128(float (&d)[64], uint64_t da, uint64_t db, int acc) {
  asm volatile("{ .reg .pred p; setp.ne.b32 p, %66, 0;\n"
    "wgmma.mma_async.sync.aligned.m64n128k16.f32.bf16.bf16 {"
    "%0, %1, %2, %3, %4, %5, %6, %7, %8, %9, %10, %11, %12, %13, %14, %15,"
    "%16, %17, %18, %19, %20, %21, %22, %23, %24, %25, %26, %27, %28, %29, %30, %31,"
    "%32, %33, %34, %35, %36, %37, %38, %39, %40, %41, %42, %43, %44, %45, %46, %47,"
    "%48, %49, %50, %51, %52, %53, %54, %55, %56, %57, %58, %59, %60, %61, %62, %63"
    "}, %64, %65, p, 1, 1, 0, %67; }"
    : "+f"(d[0]), "+f"(d[1]), "+f"(d[2]), "+f"(d[3]), "+f"(d[4]), "+f"(d[5]), "+f"(d[6]), "+f"(d[7]),
      "+f"(d[8]), "+f"(d[9]), "+f"(d[10]), "+f"(d[11]), "+f"(d[12]), "+f"(d[13]), "+f"(d[14]), "+f"(d[15]),
      "+f"(d[16]), "+f"(d[17]), "+f"(d[18]), "+f"(d[19]), "+f"(d[20]), "+f"(d[21]), "+f"(d[22]), "+f"(d[23]),
      "+f"(d[24]), "+f"(d[25]), "+f"(d[26]), "+f"(d[27]), "+f"(d[28]), "+f"(d[29]), "+f"(d[30]), "+f"(d[31]),
      "+f"(d[32]), "+f"(d[33]), "+f"(d[34]), "+f"(d[35]), "+f"(d[36]), "+f"(d[37]), "+f"(d[38]), "+f"(d[39]),
      "+f"(d[40]), "+f"(d[41]), "+f"(d[42]), "+f"(d[43]), "+f"(d[44]), "+f"(d[45]), "+f"(d[46]), "+f"(d[47]),
      "+f"(d[48]), "+f"(d[49]), "+f"(d[50]), "+f"(d[51]), "+f"(d[52]), "+f"(d[53]), "+f"(d[54]), "+f"(d[55]),
      "+f"(d[56]), "+f"(d[57]), "+f"(d[58]), "+f"(d[59]), "+f"(d[60]), "+f"(d[61]), "+f"(d[62]), "+f"(d[63])
    : "l"(da), "l"(db), "r"(acc), "n"(TB));
}
template <int TB>
__device__ __forceinline__ void wgmma_rs_n128(float (&d)[64], uint32_t a0, uint32_t a1, uint32_t a2, uint32_t a3, uint64_t db, int acc) {
  asm volatile("{ .reg .pred p; setp.ne.b32 p, %69, 0;\n"
    "wgmma.mma_async.sync.aligned.m64n128k16.f32.bf16.bf16 {"
    "%0, %1, %2, %3, %4, %5, %6, %7, %8, %9, %10, %11, %12, %13, %14, %15,"
    "%16, %17, %18, %19, %20, %21, %22, %23, %24, %25, %26, %27, %28, %29, %30, %31,"
    "%32, %33, %34, %35, %36, %37, %38, %39, %40, %41, %42, %43, %44, %45, %46, %47,"
    "%48, %49, %50, %51, %52, %53, %54, %55, %56, %57, %58, %59, %60, %61, %62, %63"
    "}, {%64, %65, %66, %67}, %68, p, 1, 1, %70; }"
    : "+f"(d[0]), "+f"(d[1]), "+f"(d[2]), "+f"(d[3]), "+f"(d[4]), "+f"(d[5]), "+f"(d[6]), "+f"(d[7]),
      "+f"(d[8]), "+f"(d[9]), "+f"(d[10]), "+f"(d[11]), "+f"(d[12]), "+f"(d[13]), "+f"(d[14]), "+f"(d[15]),
      "+f"(d[16]), "+f"(d[17]), "+f"(d[18]), "+f"(d[19]), "+f"(d[20]), "+f"(d[21]), "+f"(d[22]), "+f"(d[23]),
      "+f"(d[24]), "+f"(d[25]), "+f"(d[26]), "+f"(d[27]), "+f"(d[28]), "+f"(d[29]), "+f"(d[30]), "+f"(d[31]),
      "+f"(d[32]), "+f"(d[33]), "+f"(d[34]), "+f"(d[35]), "+f"(d[36]), "+f"(d[37]), "+f"(d[38]), "+f"(d[39]),
      "+f"(d[40]), "+f"(d[41]), "+f"(d[42]), "+f"(d[43]), "+f"(d[44]), "+f"(d[45]), "+f"(d[46]), "+f"(d[47]),
      "+f"(d[48]), "+f"(d[49]), "+f"(d[50]), "+f"(d[51]), "+f"(d[52]), "+f"(d[53]), "+f"(d[54]), "+f"(d[55]),
      "+f"(d[56]), "+f"(d[57]), "+f"(d[58]), "+f"(d[59]), "+f"(d[60]), "+f"(d[61]), "+f"(d[62]), "+f"(d[63])
    : "r"(a0), "r"(a1), "r"(a2), "r"(a3), "l"(db), "r"(acc), "n"(TB));
}

__device__ __forceinline__ void store_tile(const float (&a)[64], float r0, float r1, uint32_t row_addr, uint32_t sw) {
#pragma unroll
  for (int kk = 0; kk < 8; kk++) {
    uint32_t chunk = ((2 * kk) & 7) ^ sw;
    stsm4(row_addr + (kk >> 2) * 8192 + chunk * 16,
          pack_bf16(a[8 * kk] * r0, a[8 * kk + 1] * r0), pack_bf16(a[8 * kk + 2] * r1, a[8 * kk + 3] * r1),
          pack_bf16(a[8 * kk + 4] * r0, a[8 * kk + 5] * r0), pack_bf16(a[8 * kk + 6] * r1, a[8 * kk + 7] * r1));
  }
}

__global__ void __cluster_dims__(2, 1, 1) __launch_bounds__(384, 1)
gqa_fused_kernel(const __grid_constant__ Params p, __nv_bfloat16* __restrict__ out) {
  extern __shared__ __align__(1024) char smem_raw[];
  const uint32_t sb = (smem_u32(smem_raw) + 1023u) & ~1023u;
  const uint32_t bars = sb + OFF_BAR;
  auto bar = [&](int i) { return bars + 8u * i; };

  const int c = blockIdx.x & 1, u = blockIdx.x >> 1;
  const int r = u >> 5, g = (u >> 2) & 7, bp = u & 3;
  const int warp = __shfl_sync(~0u, (int)(threadIdx.x >> 5), 0);
  const int lane = threadIdx.x & 31;

  if (threadIdx.x == 0) {
    TR(0, 0);
#pragma unroll
    for (int i = 0; i < NSLOT; i++) { mbar_init(bar(B_FULL + i), 1); mbar_init(bar(B_EMPTY + i), 2); }
#pragma unroll
    for (int i = 0; i < 4; i++) { mbar_init(bar(B_WFULL + i), 1); mbar_init(bar(B_WEMPTY + i), 2); }
    mbar_init(bar(B_O1_READY), 256);
#pragma unroll
    for (int i = B_U3_FREE; i < B_COUNT; i++) mbar_init(bar(i), 1);
    asm volatile("fence.mbarrier_init.release.cluster;" ::: "memory");
    mbar_expect_tx(bar(B_O1_IN), UNIT);
    mbar_expect_tx(bar(B_O2_IN), UNIT / 2);
    mbar_expect_tx(bar(B_O2_IN + 1), UNIT / 2);
  }
  __syncthreads();
  cluster_arrive();

  if (warp < 4) {
    asm volatile("setmaxnreg.dec.sync.aligned.u32 24;");
    if (warp == 0) {
      if (lane == 0) {
#pragma unroll 1
        for (int t = 0; t < NSLOT; t++) {
          mbar_expect_tx(bar(B_FULL + t), 16384 + UNIT);
          tma_2d(sb + t * SLOT, &p.x[r], t * 64, bp * 128, bar(B_FULL + t));
          tma_3d(sb + t * SLOT + 16384, &p.wq[r], t * 64, 8 * g + 4 * c, bar(B_FULL + t));
        }
        prefetch_map(&p.k[r]); prefetch_map(&p.v[r]); prefetch_map(&p.wo[r]); prefetch_map(&p.out);
      }
      __syncwarp();
      cluster_wait();
      if (lane == 0) {
        int slot = 0; uint32_t ph = 0;
#pragma unroll 1
        for (int t = NSLOT; t < QSTAGES; t++) {
          mbar_wait(bar(B_EMPTY + slot), ph);
          mbar_expect_tx(bar(B_FULL + slot), 16384 + UNIT);
          tma_2d(sb + slot * SLOT, &p.x[r], t * 64, bp * 128, bar(B_FULL + slot));
          tma_3d(sb + slot * SLOT + 16384, &p.wq[r], t * 64, 8 * g + 4 * c, bar(B_FULL + slot));
          if (++slot == NSLOT) { slot = 0; ph ^= 1; }
        }
        const int row0 = (bp * 16 + g) * 2048;
#pragma unroll 1
        for (int s = 0; s < NSTEP; s++) {
          mbar_wait(bar(B_EMPTY + slot), ph);
          mbar_expect_tx(bar(B_FULL + slot), (s == 0 || s == NSTEP - 1) ? UNIT : SLOT);
          if (s < NSTEP - 1) tma_3d(sb + slot * SLOT + UNIT, &p.k[r], row0 + (s >> 4) * 16384 + (s & 15) * 128, 0, bar(B_FULL + slot));
          if (s > 0) tma_3d(sb + slot * SLOT, &p.v[r], row0 + ((s - 1) >> 4) * 16384 + ((s - 1) & 15) * 128, 0, bar(B_FULL + slot));
          if (++slot == NSLOT) { slot = 0; ph ^= 1; }
        }
        mbar_arrive_remote(mapa(bar(B_U3_FREE), c ^ 1));
        mbar_wait(bar(B_EMPTY + 2), 0);
#pragma unroll 1
        for (int i = 0; i < 16; i++) {
          if (i == 4) {
            mbar_wait(bar(B_EMPTY + 0), 1);
            mbar_arrive_remote(mapa(bar(B_U1_FREE), c ^ 1));
          }
          if (i >= 4) mbar_wait(bar(B_WEMPTY + (i & 3)), ((i >> 2) - 1) & 1);
          const int head = 4 * g + (((i >> 1) & 3) ^ (2 * c));
          mbar_expect_tx(bar(B_WFULL + (i & 3)), 16384);
          tma_3d(sb + 4 * UNIT + (i & 3) * 16384, &p.wo[r], head * 128 + (i & 1) * 64, 4 * c + 2 * (i >> 3), bar(B_WFULL + (i & 3)));
        }
      }
    } else if (warp < 3) {
      cluster_wait();
      bar_sync(NB_START0 + warp - 1, 160);
      int slot = QSTAGES % NSLOT; uint32_t ph = (QSTAGES / NSLOT) & 1;
#pragma unroll 1
      for (int s = 0; s < NSTEP; s++) {
        mbar_wait(bar(B_FULL + slot), ph);
        bar_sync(NB_PP0 + warp - 1, 288);
        if (++slot == NSLOT) { slot = 0; ph ^= 1; }
      }
    } else {
      uint4* z = reinterpret_cast<uint4*>(out + (size_t)(bp * 128 + g * 16) * 1024 + r * 512 + c * 256) + lane;
#pragma unroll
      for (int i = 0; i < 16; i++) z[i * 128] = make_uint4(0, 0, 0, 0);
      asm volatile("fence.proxy.async.global;" ::: "memory");
      __threadfence();
      __syncwarp();
      cluster_wait();
      if (lane == 0) {
        unsigned int* cnt = &g_zero_cnt[(r * 4 + bp) * 2 + c];
        const unsigned int target = (atomicAdd(cnt, 1u) & ~7u) + 8u;
        mbar_wait_sleep(bar(B_O1_READY), 0);
        unsigned int v;
        int i = 0;
        do {
          asm volatile("ld.acquire.gpu.global.u32 %0, [%1];" : "=r"(v) : "l"(cnt) : "memory");
          if (++i == SPIN_LIMIT) __trap();
        } while ((int)(v - target) < 0);
        asm volatile("fence.proxy.async.global;" ::: "memory");
        mbar_arrive(bar(B_ZERO_OK));
        mbar_wait_sleep(bar(B_U3_FREE), 0);
        mbar_wait_cluster(bar(B_U3_FREE), 0);
        dsmem_copy(mapa(sb + 3 * UNIT, c ^ 1), sb + OFF_STASH, UNIT, mapa(bar(B_O1_IN), c ^ 1));
      }
    }
  } else {
    asm volatile("setmaxnreg.inc.sync.aligned.u32 240;");
    const int w = (warp >> 2) - 1;
    const int wq = warp & 3;
    const bool leader = (threadIdx.x & 127) == 0;
    float O[64], S[64];
    uint32_t P[32], Q[32];
    const uint32_t d0 = (sb & 0x3FFFF) >> 4;
    const uint32_t dK = d0 | (1u << 16);
    const uint32_t dN8 = d0 | (512u << 16);
    const uint32_t dN16 = d0 | (1024u << 16);
    const uint32_t tile_row = (16 * wq + (lane & 7) + ((lane >> 3) & 1) * 8) * 128;
    const uint32_t tile_sw = (lane & 7) ^ (lane >> 4);
    int slot = 0; uint32_t ph = 0;

#pragma unroll 1
    for (int t = 0; t < QSTAGES; t++) {
      mbar_wait(bar(B_FULL + slot), ph);
      if (t == 0 && leader) TR(1 + w, 1);
      const uint32_t a = dK + slot * (SLOT >> 4), b = dN8 + slot * (SLOT >> 4) + ((16384 + w * 16384) >> 4);
      wg_fence();
#pragma unroll
      for (int kk = 0; kk < 4; kk++) {
        wgmma_ss_n128<1>(S, mk_desc(a + kk * 2), mk_desc(b + kk * 128), (t | kk) != 0);
        wgmma_ss_n128<1>(O, mk_desc(a + 512 + kk * 2), mk_desc(b + kk * 128), (t | kk) != 0);
      }
      wg_commit();
      if (t > 0) {
        wg_wait<1>();
        if (leader) mbar_arrive(bar(B_EMPTY + (slot ? slot - 1 : NSLOT - 1)));
      }
      if (++slot == NSLOT) { slot = 0; ph ^= 1; }
    }
    bar_arrive(NB_START0 + w, 160);
    wg_wait<0>();
    fence_regs(S); fence_regs(O);
    if (leader) mbar_arrive(bar(B_EMPTY + (slot ? slot - 1 : NSLOT - 1)));
    if (leader) TR(1 + w, 2);
    const uint32_t stash = sb + OFF_STASH + w * 16384;
    const uint32_t qst = stash + wq * 2048 + lane * 16;
#pragma unroll
    for (int i = 0; i < 32; i++) Q[i] = pack_bf16(S[2 * i], S[2 * i + 1]);
#pragma unroll
    for (int i = 0; i < 8; i++)
      asm volatile("st.shared.v4.b32 [%0], {%1, %2, %3, %4};" :: "r"(qst + (i >> 2) * 8192 + (i & 3) * 512),
                   "r"(pack_bf16(O[8 * i], O[8 * i + 1])), "r"(pack_bf16(O[8 * i + 2], O[8 * i + 3])),
                   "r"(pack_bf16(O[8 * i + 4], O[8 * i + 5])), "r"(pack_bf16(O[8 * i + 6], O[8 * i + 7])) : "memory");
    fence_regs(Q);
    cluster_wait();

    const float cs = 0.08838834764831845f * 1.4426950408889634f;
    float b0, b1, l0 = 0.f, l1 = 0.f, s0, s1;
    auto issue_qk = [&]() {
      const uint32_t kb = dK + slot * (SLOT >> 4) + (UNIT >> 4);
#pragma unroll
      for (int kk = 0; kk < 8; kk++)
        wgmma_rs_n128<0>(S, Q[4 * kk], Q[4 * kk + 1], Q[4 * kk + 2], Q[4 * kk + 3], mk_desc(kb + (kk >> 2) * 1024 + (kk & 3) * 2), kk > 0);
    };
    auto issue_pv = [&](int acc) {
      const uint32_t vb = dN16 + slot * (SLOT >> 4);
#pragma unroll
      for (int kk = 0; kk < 8; kk++)
        wgmma_rs_n128<1>(O, P[4 * kk], P[4 * kk + 1], P[4 * kk + 2], P[4 * kk + 3], mk_desc(vb + kk * 128), kk > 0 ? 1 : acc);
    };
    auto finish_step = [&]() {
      wg_wait<0>();
      fence_regs(S); fence_regs(O); fence_regs(P); fence_regs(Q);
      if (leader) mbar_arrive(bar(B_EMPTY + slot));
      if (++slot == NSLOT) slot = 0;
    };
    auto expo = [&]() {
#pragma unroll
      for (int i = 0; i < 64; i += 4) {
        const float e0 = ex2(fmaf(S[i], cs, b0)), e1 = ex2(fmaf(S[i + 1], cs, b0));
        const float e2 = ex2(fmaf(S[i + 2], cs, b1)), e3 = ex2(fmaf(S[i + 3], cs, b1));
        if (!SUM_HADD2) {
          if (i) { s0 += e0; s1 += e2; } else { s0 = e0; s1 = e2; }
          s0 += e1; s1 += e3;
        }
        P[i / 2] = pack_bf16(e0, e1); P[i / 2 + 1] = pack_bf16(e2, e3);
      }
      if (SUM_HADD2) {
        uint32_t h[16];
#pragma unroll
        for (int i = 0; i < 8; i++) { h[2 * i] = hadd2(P[4 * i], P[4 * i + 2]); h[2 * i + 1] = hadd2(P[4 * i + 1], P[4 * i + 3]); }
#pragma unroll
        for (int i = 0; i < 4; i++) { h[2 * i] = hadd2(h[4 * i], h[4 * i + 2]); h[2 * i + 1] = hadd2(h[4 * i + 1], h[4 * i + 3]); }
#pragma unroll
        for (int i = 0; i < 2; i++) { h[2 * i] = hadd2(h[4 * i], h[4 * i + 2]); h[2 * i + 1] = hadd2(h[4 * i + 1], h[4 * i + 3]); }
        h[0] = hadd2(h[0], h[2]); h[1] = hadd2(h[1], h[3]);
        s0 = __uint_as_float(h[0] << 16) + __uint_as_float(h[0] & 0xffff0000u);
        s1 = __uint_as_float(h[1] << 16) + __uint_as_float(h[1] & 0xffff0000u);
      }
    };
    auto tile_max = [&](float& n0, float& n1) {
      float p0 = fmaxf(S[0], S[1]), p1 = fmaxf(S[2], S[3]), q0 = fmaxf(S[4], S[5]), q1 = fmaxf(S[6], S[7]);
#pragma unroll
      for (int i = 8; i < 64; i += 8) {
        p0 = fmaxf(p0, fmaxf(S[i], S[i + 1])); p1 = fmaxf(p1, fmaxf(S[i + 2], S[i + 3]));
        q0 = fmaxf(q0, fmaxf(S[i + 4], S[i + 5])); q1 = fmaxf(q1, fmaxf(S[i + 6], S[i + 7]));
      }
      n0 = fmaxf(p0, q0); n1 = fmaxf(p1, q1);
      n0 = fmaxf(n0, __shfl_xor_sync(~0u, n0, 1)); n1 = fmaxf(n1, __shfl_xor_sync(~0u, n1, 1));
      n0 = fmaxf(n0, __shfl_xor_sync(~0u, n0, 2)); n1 = fmaxf(n1, __shfl_xor_sync(~0u, n1, 2));
      n0 *= -cs; n1 *= -cs;
    };
    auto row_norms = [&](float& r0, float& r1) {
      l0 += __shfl_xor_sync(~0u, l0, 1); l1 += __shfl_xor_sync(~0u, l1, 1);
      l0 += __shfl_xor_sync(~0u, l0, 2); l1 += __shfl_xor_sync(~0u, l1, 2);
      r0 = __frcp_rn(l0); r1 = __frcp_rn(l1);
    };

    if (w == 1) bar_arrive(NB_PP0, 288);
    bar_sync(NB_PP0 + w, 288);
    wg_fence(); issue_qk(); wg_commit();
    bar_arrive(NB_PP0 + 1 - w, 288);
    finish_step();
    if (leader) TR(1 + w, 3);
#pragma unroll 1
    for (int pass = 0; pass < 2; pass++) {
      tile_max(b0, b1);
      expo();
      l0 = s0; l1 = s1;
      fence_regs(P);
#pragma unroll 1
      for (int j = 1; j < 16; j++) {
        bar_sync(NB_PP0 + w, 288);
        wg_fence(); issue_qk(); issue_pv(j > 1); wg_commit();
        bar_arrive(NB_PP0 + 1 - w, 288);
        finish_step();
        expo();
        if (__any_sync(~0u, !(s0 + s1 <= SUM_LIMIT))) {
          float n0, n1;
          tile_max(n0, n1);
          n0 = fminf(n0, b0); n1 = fminf(n1, b1);
          const float a0 = ex2(n0 - b0), a1 = ex2(n1 - b1);
          b0 = n0; b1 = n1; l0 *= a0; l1 *= a1;
#pragma unroll
          for (int i = 0; i < 64; i += 4) { O[i] *= a0; O[i + 1] *= a0; O[i + 2] *= a1; O[i + 3] *= a1; }
          expo();
        }
        l0 += s0; l1 += s1;
        fence_regs(P); fence_regs(O);
      }
      if (pass == 0) {
#pragma unroll
        for (int i = 0; i < 8; i++)
          asm volatile("ld.shared.v4.b32 {%0, %1, %2, %3}, [%4];" : "=r"(Q[4 * i]), "=r"(Q[4 * i + 1]), "=r"(Q[4 * i + 2]), "=r"(Q[4 * i + 3])
                       : "r"(qst + (i >> 2) * 8192 + (i & 3) * 512) : "memory");
        fence_regs(Q);
        bar_sync(NB_PP0 + w, 288);
        wg_fence(); issue_qk(); issue_pv(1); wg_commit();
        bar_arrive(NB_PP0 + 1 - w, 288);
        float r0, r1;
        row_norms(r0, r1);
        finish_step();
        store_tile(O, r0, r1, stash + tile_row, tile_sw);
        fence_async_smem();
        mbar_arrive(bar(B_O1_READY));
        if (leader) TR(1 + w, 4);
      }
    }
    bar_sync(NB_PP0 + w, 288);
    wg_fence(); issue_pv(1); wg_commit();
    if (w == 0) bar_arrive(NB_PP0 + 1, 288);
    {
      float r0, r1;
      row_norms(r0, r1);
      mbar_wait(bar(B_EMPTY + 0), 1);
      finish_step();
      if (leader) TR(1 + w, 5);
      store_tile(O, r0, r1, sb + w * 16384 + tile_row, tile_sw);
    }
    fence_async_smem();
    bar_sync(NB_WG0 + w, 128);
    if (leader) {
      if (w == 0) mbar_arrive(bar(B_O2_OWN0));
      mbar_wait_cluster(bar(B_U1_FREE), 0);
      dsmem_copy(mapa(sb + UNIT + w * 16384, c ^ 1), sb + w * 16384, 16384, mapa(bar(B_O2_IN + w), c ^ 1));
    }
    __syncwarp();

    if (w == 1) mbar_wait(bar(B_O2_OWN0), 0);
    const uint32_t a_own = dK + ((w ? 0 : OFF_STASH) >> 4), a_peer = dK + ((w ? UNIT : 3 * UNIT) >> 4);
    const uint32_t stage = sb + 2 * UNIT + w * 16384;
    auto oproj_sub = [&](float (&acc)[64], int i) {
      mbar_wait(bar(B_WFULL + (i & 3)), (i >> 2) & 1);
      const uint32_t a = ((i & 4) ? a_peer : a_own) + (i & 3) * 512, b = dN8 + ((4 * UNIT) >> 4) + (i & 3) * 1024;
      wg_fence();
#pragma unroll
      for (int kk = 0; kk < 4; kk++) wgmma_ss_n128<1>(acc, mk_desc(a + kk * 2), mk_desc(b + kk * 128), ((i & 7) | kk) != 0);
      wg_commit();
      if (i > 0) {
        wg_wait<1>();
        if (leader) mbar_arrive(bar(B_WEMPTY + ((i - 1) & 3)));
      }
    };
#pragma unroll 1
    for (int i = 0; i < 8; i++) {
      if (i == 4) mbar_wait_cluster(bar(w ? B_O2_IN : B_O1_IN), 0);
      if (i == 6 && w) mbar_wait_cluster(bar(B_O2_IN + 1), 0);
      oproj_sub(S, i);
    }
    cluster_arrive();
    oproj_sub(O, 8);
    fence_regs(S);
    if (leader) TR(1 + w, 6);
    mbar_wait(bar(B_EMPTY + 1), 1);
    store_tile(S, 1.f, 1.f, stage + tile_row, tile_sw);
    fence_async_smem();
    bar_sync(NB_WG0 + w, 128);
    if (leader) {
      mbar_wait(bar(B_ZERO_OK), 0);
      tma_red_3d(&p.out, (2 * bp + w) * 64, r * 8 + c * 4, stage);
      asm volatile("cp.async.bulk.commit_group;" ::: "memory");
    }
    __syncwarp();
#pragma unroll 1
    for (int i = 9; i < 16; i++) oproj_sub(O, i);
    if (leader) asm volatile("cp.async.bulk.wait_group.read 0;" ::: "memory");
    bar_sync(NB_WG0 + w, 128);
    wg_wait<0>();
    fence_regs(O);
    if (leader) TR(1 + w, 7);
    store_tile(O, 1.f, 1.f, stage + tile_row, tile_sw);
    fence_async_smem();
    bar_sync(NB_WG0 + w, 128);
    if (leader) {
      tma_red_3d(&p.out, (2 * bp + w) * 64, r * 8 + c * 4 + 2, stage);
      asm volatile("cp.async.bulk.commit_group;" ::: "memory");
      asm volatile("cp.async.bulk.wait_group.read 0;" ::: "memory");
      TR(1 + w, 8);
    }
    __syncwarp();
    cluster_wait();
  }
}

typedef CUresult (*EncodeFn)(CUtensorMap*, CUtensorMapDataType, cuuint32_t, void*, const cuuint64_t*, const cuuint64_t*,
                             const cuuint32_t*, const cuuint32_t*, CUtensorMapInterleave, CUtensorMapSwizzle,
                             CUtensorMapL2promotion, CUtensorMapFloatOOBfill);

void encode_3d(EncodeFn fn, CUtensorMap* m, const void* ptr, uint64_t rows, uint64_t cols, uint32_t box_rows, uint32_t groups) {
  cuuint64_t dims[3] = {64, rows, cols / 64};
  cuuint64_t strides[2] = {cols * 2, 128};
  cuuint32_t box[3] = {64, box_rows, groups};
  cuuint32_t es[3] = {1, 1, 1};
  fn(m, CU_TENSOR_MAP_DATA_TYPE_BFLOAT16, 3, const_cast<void*>(ptr), dims, strides, box, es, CU_TENSOR_MAP_INTERLEAVE_NONE,
     CU_TENSOR_MAP_SWIZZLE_128B, CU_TENSOR_MAP_L2_PROMOTION_L2_128B, CU_TENSOR_MAP_FLOAT_OOB_FILL_NONE);
}
void encode_2d(EncodeFn fn, CUtensorMap* m, const void* ptr, uint64_t rows, uint64_t cols, uint32_t box_rows) {
  cuuint64_t dims[2] = {cols, rows};
  cuuint64_t strides[1] = {cols * 2};
  cuuint32_t box[2] = {64, box_rows};
  cuuint32_t es[2] = {1, 1};
  fn(m, CU_TENSOR_MAP_DATA_TYPE_BFLOAT16, 2, const_cast<void*>(ptr), dims, strides, box, es, CU_TENSOR_MAP_INTERLEAVE_NONE,
     CU_TENSOR_MAP_SWIZZLE_128B, CU_TENSOR_MAP_L2_PROMOTION_L2_128B, CU_TENSOR_MAP_FLOAT_OOB_FILL_NONE);
}

}

extern "C" void kernel_launch(void* const* d_in, const int* in_sizes, int n_in, void* d_out, int out_size) {
  (void)in_sizes; (void)n_in; (void)out_size;
  static EncodeFn encode = nullptr;
  if (!encode) {
    void* fn = nullptr;
    cudaDriverEntryPointQueryResult q;
    cudaGetDriverEntryPoint("cuTensorMapEncodeTiled", &fn, cudaEnableDefault, &q);
    encode = (EncodeFn)fn;
    cudaFuncSetAttribute(gqa_fused_kernel, cudaFuncAttributeMaxDynamicSharedMemorySize, SMEM_BYTES);
  }
  Params p;
  for (int r = 0; r < 2; r++) {
    void* const* in = d_in + 5 * r;
    encode_2d(encode, &p.x[r], in[0], 512, 512, 128);
    encode_3d(encode, &p.k[r], in[1], 131072, 128, 128, 2);
    encode_3d(encode, &p.v[r], in[2], 131072, 128, 128, 2);
    encode_3d(encode, &p.wq[r], in[3], 512, 4096, 64, 4);
    encode_3d(encode, &p.wo[r], in[4], 4096, 512, 64, 2);
  }
  encode_3d(encode, &p.out, d_out, 512, 1024, 64, 2);
  gqa_fused_kernel<<<128, 384, SMEM_BYTES, cudaStreamPerThread>>>(p, (__nv_bfloat16*)d_out);
}
```

```cpp
#include <cuda_runtime.h>
#include <cuda.h>
#include <cuda_bf16.h>
#include <stdint.h>
#include <type_traits>

#define SUM_HADD2 0
#define PF_MODE 1
#define PF_DIST 6
#define PF_W 0
#define PF_START 2
#define PF_QW 1000
#define EF 1
#define MAP 1
#define OREL 1
#define EARLY 1
#define STAGE_LINES 8
#define STAGE_AT 6000
#define STAGE_END 32
#define OPIPE 1
#define QORDER 1
#define EARLYQ 2
#define OGO 15
#define TRACE 0

namespace {

constexpr int UNIT = 32768;
constexpr int SLOT = 2 * UNIT;
constexpr int NSLOT = 3;
constexpr int OFF_STASH = 5 * UNIT;
constexpr int OFF_BAR = 7 * UNIT;
constexpr int SMEM_BYTES = OFF_BAR + 512 + 1024;
constexpr int QSTAGES = 8;
constexpr int QBUF = 49152;
constexpr int NSTEP = 33;
constexpr float SUM_LIMIT = 4096.f;
constexpr int SPIN_LIMIT = 1 << 22;

enum { B_FULL = 0, B_EMPTY = 3, B_QFULL = 6, B_QEMPTY = 10, B_WFULL = 14, B_WEMPTY = 20, B_O1_READY = 26, B_O2_READY = 27,
       B_STAGE_READY = 29, B_PEER1_FREE = 31, B_PEER2_FREE = 32, B_O1_IN = 33, B_O2_IN = 34, B_ZERO_OK = 36, B_COUNT = 37 };
enum { NB_PP0 = 1, NB_WG0 = 3, NB_QORD = 5 };

__device__ __forceinline__ uint32_t v_unit(int slot) { return slot == 2 ? 6 : 2 * slot + 1; }
__device__ __forceinline__ int w_buf(int i) { return i < 6 ? i : i < 12 ? i - 6 : i - 12; }
__device__ __forceinline__ uint32_t w_phase(int i) { return i >= 6 && i < 12; }
__device__ __forceinline__ int w_peer(int i) { return ((i + 4) >> 3) & 1; }
__device__ __forceinline__ uint32_t w_off(int buf) { return (buf < 2 ? 0 : buf < 4 ? 6 * UNIT : 3 * UNIT) + (buf & 1) * 16384; }

struct Params {
  CUtensorMap x[2], wq[2], k[2], v[2], wo[2], out;
  const char* kv_ptr[2][2];
  const char *x_ptr[2], *wq_ptr[2], *wo_ptr[2];
};

__device__ unsigned int g_zero_cnt[16];

__device__ __forceinline__ uint32_t smem_u32(const void* p) { return (uint32_t)__cvta_generic_to_shared(p); }
__device__ __forceinline__ void mbar_init(uint32_t bar, uint32_t cnt) { asm volatile("mbarrier.init.shared::cta.b64 [%0], %1;" :: "r"(bar), "r"(cnt)); }
__device__ __forceinline__ void mbar_expect_tx(uint32_t bar, uint32_t bytes) { asm volatile("mbarrier.arrive.expect_tx.shared::cta.b64 _, [%0], %1;" :: "r"(bar), "r"(bytes) : "memory"); }
__device__ __forceinline__ void mbar_arrive(uint32_t bar) { asm volatile("mbarrier.arrive.shared::cta.b64 _, [%0];" :: "r"(bar) : "memory"); }
__device__ __forceinline__ uint32_t mapa(uint32_t addr, uint32_t cta) { uint32_t r; asm("mapa.shared::cluster.u32 %0, %1, %2;" : "=r"(r) : "r"(addr), "r"(cta)); return r; }
__device__ __forceinline__ void mbar_arrive_remote(uint32_t rbar) { asm volatile("mbarrier.arrive.shared::cluster.b64 _, [%0];" :: "r"(rbar) : "memory"); }
__device__ __forceinline__ bool mbar_try(uint32_t bar, uint32_t parity) {
  uint32_t ok;
  asm volatile("{ .reg .pred p; mbarrier.try_wait.parity.shared::cta.b64 p, [%1], %2; selp.u32 %0, 1, 0, p; }" : "=r"(ok) : "r"(bar), "r"(parity) : "memory");
  return ok;
}
__device__ __forceinline__ bool mbar_try_cluster(uint32_t bar, uint32_t parity) {
  uint32_t ok;
  asm volatile("{ .reg .pred p; mbarrier.try_wait.parity.acquire.cluster.shared::cta.b64 p, [%1], %2; selp.u32 %0, 1, 0, p; }" : "=r"(ok) : "r"(bar), "r"(parity) : "memory");
  return ok;
}
__device__ __forceinline__ void mbar_wait(uint32_t bar, uint32_t parity) {
  if (mbar_try(bar, parity)) return;
#pragma unroll 1
  for (int i = 0; i < SPIN_LIMIT; i++) if (mbar_try(bar, parity)) return;
  __trap();
}
__device__ __forceinline__ void mbar_wait_sleep(uint32_t bar, uint32_t parity) {
#pragma unroll 1
  for (int i = 0; i < SPIN_LIMIT; i++) { if (mbar_try(bar, parity)) return; __nanosleep(200); }
  __trap();
}
__device__ __forceinline__ void mbar_wait_cluster(uint32_t bar, uint32_t parity) {
#pragma unroll 1
  for (int i = 0; i < SPIN_LIMIT; i++) if (mbar_try_cluster(bar, parity)) return;
  __trap();
}
__device__ __forceinline__ void tma_2d(uint32_t dst, const CUtensorMap* m, int c0, int c1, uint32_t bar) {
  asm volatile("cp.async.bulk.tensor.2d.shared::cluster.global.mbarrier::complete_tx::bytes [%0], [%1, {%3, %4}], [%2];"
    :: "r"(dst), "l"(m), "r"(bar), "r"(c0), "r"(c1) : "memory");
}
__device__ __forceinline__ void tma_3d(uint32_t dst, const CUtensorMap* m, int c1, int c2, uint32_t bar) {
  asm volatile("cp.async.bulk.tensor.3d.shared::cluster.global.mbarrier::complete_tx::bytes [%0], [%1, {%3, %4, %5}], [%2];"
    :: "r"(dst), "l"(m), "r"(bar), "r"(0), "r"(c1), "r"(c2) : "memory");
}
__device__ __forceinline__ void tma_3d_hint(uint32_t dst, const CUtensorMap* m, int c1, int c2, uint32_t bar, uint64_t pol) {
  asm volatile("cp.async.bulk.tensor.3d.shared::cluster.global.mbarrier::complete_tx::bytes.L2::cache_hint [%0], [%1, {%3, %4, %5}], [%2], %6;"
    :: "r"(dst), "l"(m), "r"(bar), "r"(0), "r"(c1), "r"(c2), "l"(pol) : "memory");
}
__device__ __forceinline__ void tma_red_3d(const CUtensorMap* m, int c1, int c2, uint32_t src) {
  asm volatile("cp.reduce.async.bulk.tensor.3d.global.shared::cta.add.tile.bulk_group [%0, {%2, %3, %4}], [%1];"
    :: "l"(m), "r"(src), "r"(0), "r"(c1), "r"(c2) : "memory");
}
__device__ __forceinline__ void dsmem_copy(uint32_t rdst, uint32_t src, uint32_t bytes, uint32_t rbar) {
  asm volatile("cp.async.bulk.shared::cluster.shared::cta.mbarrier::complete_tx::bytes [%0], [%1], %2, [%3];"
    :: "r"(rdst), "r"(src), "r"(bytes), "r"(rbar) : "memory");
}
__device__ __forceinline__ void prefetch_map(const CUtensorMap* m) { asm volatile("prefetch.tensormap [%0];" :: "l"(m) : "memory"); }
__device__ __forceinline__ void prefetch_l2(const char* p) { asm volatile("prefetch.global.L2 [%0];" :: "l"(p) : "memory"); }
__device__ __forceinline__ void prefetch_tile(const char* base, int lane) {
  if (PF_MODE == 1) {
#pragma unroll
    for (int i = 0; i < 8; i++) prefetch_l2(base + (i * 32 + lane) * 128);
  } else if (PF_MODE == 2) {
#pragma unroll
    for (int i = 0; i < 16; i++) prefetch_l2(base + (i * 32 + lane) * 64);
  } else if (PF_MODE == 3) {
    if (lane == 0) asm volatile("cp.async.bulk.prefetch.L2.global [%0], %1;" :: "l"(base), "r"(32768) : "memory");
  } else if (PF_MODE == 4) {
    asm volatile("cp.async.bulk.prefetch.L2.global [%0], %1;" :: "l"(base + lane * 1024), "r"(1024) : "memory");
  } else if (PF_MODE == 5) {
#pragma unroll
    for (int i = 0; i < 4; i++) prefetch_l2(base + (i * 32 + lane) * 256);
  }
}
__device__ __forceinline__ void fence_async_smem() { asm volatile("fence.proxy.async.shared::cta;" ::: "memory"); }
__device__ __forceinline__ void bar_sync(int id, int n) { asm volatile("bar.sync %0, %1;" :: "r"(id), "r"(n) : "memory"); }
__device__ __forceinline__ void bar_arrive(int id, int n) { asm volatile("bar.arrive %0, %1;" :: "r"(id), "r"(n) : "memory"); }
__device__ __forceinline__ void cluster_arrive() { asm volatile("barrier.cluster.arrive.relaxed.aligned;" ::: "memory"); }
__device__ __forceinline__ void cluster_wait() { asm volatile("barrier.cluster.wait.aligned;" ::: "memory"); }
__device__ __forceinline__ void wg_fence() { asm volatile("wgmma.fence.sync.aligned;" ::: "memory"); }
__device__ __forceinline__ void wg_commit() { asm volatile("wgmma.commit_group.sync.aligned;" ::: "memory"); }
template <int N> __device__ __forceinline__ void wg_wait() { asm volatile("wgmma.wait_group.sync.aligned %0;" :: "n"(N) : "memory"); }
template <int N> __device__ __forceinline__ void fence_regs(float (&d)[N]) {
#pragma unroll
  for (int i = 0; i < N; i++) asm volatile("" : "+f"(d[i]) :: "memory");
}
template <int N> __device__ __forceinline__ void fence_regs(uint32_t (&d)[N]) {
#pragma unroll
  for (int i = 0; i < N; i++) asm volatile("" : "+r"(d[i]) :: "memory");
}
__device__ __forceinline__ uint64_t mk_desc(uint32_t lo) { return ((uint64_t)0x40000040u << 32) | lo; }
__device__ __forceinline__ float ex2(float x) { float y; asm("ex2.approx.ftz.f32 %0, %1;" : "=f"(y) : "f"(x)); return y; }
__device__ __forceinline__ uint32_t pack_bf16(float lo, float hi) { uint32_t r; asm("cvt.rn.bf16x2.f32 %0, %1, %2;" : "=r"(r) : "f"(hi), "f"(lo)); return r; }
__device__ __forceinline__ uint32_t hadd2(uint32_t a, uint32_t b) { uint32_t r; asm("add.rn.bf16x2 %0, %1, %2;" : "=r"(r) : "r"(a), "r"(b)); return r; }
__device__ __forceinline__ void stsm4(uint32_t addr, uint32_t a, uint32_t b, uint32_t c, uint32_t d) {
  asm volatile("stmatrix.sync.aligned.m8n8.x4.shared.b16 [%0], {%1, %2, %3, %4};" :: "r"(addr), "r"(a), "r"(b), "r"(c), "r"(d) : "memory");
}
#define TR(who, i) do {} while (0)

template <int TB>
__device__ __forceinline__ void wgmma_ss_n128(float (&d)[64], uint64_t da, uint64_t db, int acc) {
  asm volatile("{ .reg .pred p; setp.ne.b32 p, %66, 0;\n"
    "wgmma.mma_async.sync.aligned.m64n128k16.f32.bf16.bf16 {"
    "%0, %1, %2, %3, %4, %5, %6, %7, %8, %9, %10, %11, %12, %13, %14, %15,"
    "%16, %17, %18, %19, %20, %21, %22, %23, %24, %25, %26, %27, %28, %29, %30, %31,"
    "%32, %33, %34, %35, %36, %37, %38, %39, %40, %41, %42, %43, %44, %45, %46, %47,"
    "%48, %49, %50, %51, %52, %53, %54, %55, %56, %57, %58, %59, %60, %61, %62, %63"
    "}, %64, %65, p, 1, 1, 0, %67; }"
    : "+f"(d[0]), "+f"(d[1]), "+f"(d[2]), "+f"(d[3]), "+f"(d[4]), "+f"(d[5]), "+f"(d[6]), "+f"(d[7]),
      "+f"(d[8]), "+f"(d[9]), "+f"(d[10]), "+f"(d[11]), "+f"(d[12]), "+f"(d[13]), "+f"(d[14]), "+f"(d[15]),
      "+f"(d[16]), "+f"(d[17]), "+f"(d[18]), "+f"(d[19]), "+f"(d[20]), "+f"(d[21]), "+f"(d[22]), "+f"(d[23]),
      "+f"(d[24]), "+f"(d[25]), "+f"(d[26]), "+f"(d[27]), "+f"(d[28]), "+f"(d[29]), "+f"(d[30]), "+f"(d[31]),
      "+f"(d[32]), "+f"(d[33]), "+f"(d[34]), "+f"(d[35]), "+f"(d[36]), "+f"(d[37]), "+f"(d[38]), "+f"(d[39]),
      "+f"(d[40]), "+f"(d[41]), "+f"(d[42]), "+f"(d[43]), "+f"(d[44]), "+f"(d[45]), "+f"(d[46]), "+f"(d[47]),
      "+f"(d[48]), "+f"(d[49]), "+f"(d[50]), "+f"(d[51]), "+f"(d[52]), "+f"(d[53]), "+f"(d[54]), "+f"(d[55]),
      "+f"(d[56]), "+f"(d[57]), "+f"(d[58]), "+f"(d[59]), "+f"(d[60]), "+f"(d[61]), "+f"(d[62]), "+f"(d[63])
    : "l"(da), "l"(db), "r"(acc), "n"(TB));
}
template <int TB>
__device__ __forceinline__ void wgmma_rs_n128(float (&d)[64], uint32_t a0, uint32_t a1, uint32_t a2, uint32_t a3, uint64_t db, int acc) {
  asm volatile("{ .reg .pred p; setp.ne.b32 p, %69, 0;\n"
    "wgmma.mma_async.sync.aligned.m64n128k16.f32.bf16.bf16 {"
    "%0, %1, %2, %3, %4, %5, %6, %7, %8, %9, %10, %11, %12, %13, %14, %15,"
    "%16, %17, %18, %19, %20, %21, %22, %23, %24, %25, %26, %27, %28, %29, %30, %31,"
    "%32, %33, %34, %35, %36, %37, %38, %39, %40, %41, %42, %43, %44, %45, %46, %47,"
    "%48, %49, %50, %51, %52, %53, %54, %55, %56, %57, %58, %59, %60, %61, %62, %63"
    "}, {%64, %65, %66, %67}, %68, p, 1, 1, %70; }"
    : "+f"(d[0]), "+f"(d[1]), "+f"(d[2]), "+f"(d[3]), "+f"(d[4]), "+f"(d[5]), "+f"(d[6]), "+f"(d[7]),
      "+f"(d[8]), "+f"(d[9]), "+f"(d[10]), "+f"(d[11]), "+f"(d[12]), "+f"(d[13]), "+f"(d[14]), "+f"(d[15]),
      "+f"(d[16]), "+f"(d[17]), "+f"(d[18]), "+f"(d[19]), "+f"(d[20]), "+f"(d[21]), "+f"(d[22]), "+f"(d[23]),
      "+f"(d[24]), "+f"(d[25]), "+f"(d[26]), "+f"(d[27]), "+f"(d[28]), "+f"(d[29]), "+f"(d[30]), "+f"(d[31]),
      "+f"(d[32]), "+f"(d[33]), "+f"(d[34]), "+f"(d[35]), "+f"(d[36]), "+f"(d[37]), "+f"(d[38]), "+f"(d[39]),
      "+f"(d[40]), "+f"(d[41]), "+f"(d[42]), "+f"(d[43]), "+f"(d[44]), "+f"(d[45]), "+f"(d[46]), "+f"(d[47]),
      "+f"(d[48]), "+f"(d[49]), "+f"(d[50]), "+f"(d[51]), "+f"(d[52]), "+f"(d[53]), "+f"(d[54]), "+f"(d[55]),
      "+f"(d[56]), "+f"(d[57]), "+f"(d[58]), "+f"(d[59]), "+f"(d[60]), "+f"(d[61]), "+f"(d[62]), "+f"(d[63])
    : "r"(a0), "r"(a1), "r"(a2), "r"(a3), "l"(db), "r"(acc), "n"(TB));
}

template <int K0 = 0, int K1 = 8>
__device__ __forceinline__ void store_tile(const float (&a)[64], float r0, float r1, uint32_t row_addr, uint32_t sw) {
#pragma unroll
  for (int kk = K0; kk < K1; kk++) {
    uint32_t chunk = ((2 * kk) & 7) ^ sw;
    stsm4(row_addr + (kk >> 2) * 8192 + chunk * 16,
          pack_bf16(a[8 * kk] * r0, a[8 * kk + 1] * r0), pack_bf16(a[8 * kk + 2] * r1, a[8 * kk + 3] * r1),
          pack_bf16(a[8 * kk + 4] * r0, a[8 * kk + 5] * r0), pack_bf16(a[8 * kk + 6] * r1, a[8 * kk + 7] * r1));
  }
}

__global__ void __cluster_dims__(2, 1, 1) __launch_bounds__(384, 1)
gqa_fused_kernel(const __grid_constant__ Params p, __nv_bfloat16* __restrict__ out) {
  extern __shared__ __align__(1024) char smem_raw[];
  const uint32_t sb = (smem_u32(smem_raw) + 1023u) & ~1023u;
  const uint32_t bars = sb + OFF_BAR;
  auto bar = [&](int i) { return bars + 8u * i; };

  const int c = blockIdx.x & 1, u = blockIdx.x >> 1;
  int r, g, bp;
  if (u < 4) { r = 1; g = 7; bp = u; }
  else if (u < 36) { const int i = (u - 4) & 7; bp = (u - 4) >> 3; r = i >> 2; g = i & 3; }
  else { bp = (u - 36) / 7; const int j = (u - 36) - 7 * bp; r = j >> 2; g = 4 + (j & 3); }
  const int warp = __shfl_sync(~0u, (int)(threadIdx.x >> 5), 0);
  const int lane = threadIdx.x & 31;

  auto load_q = [&](int t) {
    const uint32_t dst = sb + UNIT + (t & 3) * QBUF, fb = bar(B_QFULL + (t & 3));
    mbar_expect_tx(fb, QBUF);
    tma_3d(dst + 16384, &p.wq[r], t * 64, 8 * g + 4 * c, fb);
    tma_2d(dst, &p.x[r], t * 64, bp * 128, fb);
  };
  if (warp == 1 && lane < 3) prefetch_map(lane == 0 ? &p.wq[r] : lane == 1 ? &p.x[r] : &p.k[r]);
  if (threadIdx.x == 0) {
    TR(0, 0);
#pragma unroll
    for (int i = 0; i < 4; i++) mbar_init(bar(B_QFULL + i), 1);
    asm volatile("fence.mbarrier_init.release.cluster;" ::: "memory");
    fence_async_smem();
#pragma unroll 1
    for (int t = 0; t < EARLYQ; t++) load_q(t);
#pragma unroll
    for (int i = 0; i < 4; i++) mbar_init(bar(B_QEMPTY + i), 2);
#pragma unroll
    for (int i = 0; i < NSLOT; i++) { mbar_init(bar(B_FULL + i), 1); mbar_init(bar(B_EMPTY + i), 2); }
#pragma unroll
    for (int i = 0; i < 6; i++) { mbar_init(bar(B_WFULL + i), 1); mbar_init(bar(B_WEMPTY + i), 2); }
    mbar_init(bar(B_O1_READY), 256);
#pragma unroll
    for (int i = B_O2_READY; i < B_PEER1_FREE; i++) mbar_init(bar(i), 128);
#pragma unroll
    for (int i = B_PEER1_FREE; i < B_COUNT; i++) mbar_init(bar(i), 1);
    asm volatile("fence.mbarrier_init.release.cluster;" ::: "memory");
    mbar_expect_tx(bar(B_O1_IN), UNIT);
    mbar_expect_tx(bar(B_O2_IN), UNIT / 2);
    mbar_expect_tx(bar(B_O2_IN + 1), UNIT / 2);
  }
  __syncthreads();
  cluster_arrive();

  if (warp < 4) {
    asm volatile("setmaxnreg.dec.sync.aligned.u32 24;");
    if (warp == 0) {
      const int row0 = (bp * 16 + g) * 2048;
      uint64_t pol;
      asm volatile("createpolicy.fractional.L2::evict_first.b64 %0, 1.0;" : "=l"(pol));
      auto load_k = [&](int n, int slot) { tma_3d_hint(sb + slot * SLOT, &p.k[r], row0 + (n >> 4) * 16384 + (n & 15) * 128, 0, bar(B_FULL + slot), pol); };
      auto load_v = [&](int n, int vslot, int slot) { tma_3d_hint(sb + v_unit(vslot) * UNIT, &p.v[r], row0 + (n >> 4) * 16384 + (n & 15) * 128, 0, bar(B_FULL + slot), pol); };
      if (lane == 0) {
        TR(0, 1);
#pragma unroll 1
        for (int t = EARLYQ; t < 4; t++) load_q(t);
        mbar_expect_tx(bar(B_FULL), UNIT);
        load_k(0, 0);
        TR(0, 2);
        prefetch_map(&p.v[r]); prefetch_map(&p.wo[r]); prefetch_map(&p.out);
      }
      __syncwarp();
      cluster_wait();
      if (lane == 0) {
#pragma unroll 1
        for (int t = 4; t < QSTAGES; t++) { mbar_wait(bar(B_QEMPTY + (t & 3)), 0); load_q(t); }
        mbar_expect_tx(bar(B_FULL + 1), SLOT);
        mbar_expect_tx(bar(B_FULL + 2), SLOT);
        mbar_wait(bar(B_QEMPTY + 0), 1);
        load_v(0, 0, 1);
        mbar_wait(bar(B_QEMPTY + 1), 1);
        load_k(1, 1);
        load_v(1, 1, 2);
        mbar_wait(bar(B_QEMPTY + 2), 1);
        load_k(2, 2);
        int slot = 0, vslot = 2; uint32_t ph = 0;
#pragma unroll 1
        for (int s = 3; s < NSTEP; s++) {
          mbar_wait(bar(B_EMPTY + slot), ph);
          mbar_expect_tx(bar(B_FULL + slot), s == NSTEP - 1 ? UNIT : SLOT);
          if (s < NSTEP - 1) load_k(s, slot);
          load_v(s - 1, vslot, slot);
          vslot = slot;
          if (++slot == NSLOT) { slot = 0; ph ^= 1; }
        }
        mbar_arrive_remote(mapa(bar(B_PEER1_FREE), c ^ 1));
        mbar_wait(bar(B_EMPTY + 0), 0);
#pragma unroll 1
        for (int i = 0; i < 16; i++) {
          const int buf = w_buf(i);
          if (i == 4) {
            mbar_wait(bar(B_EMPTY + 1), 0);
            mbar_arrive_remote(mapa(bar(B_PEER2_FREE), c ^ 1));
            mbar_wait(bar(B_EMPTY + 2), 0);
          }
          if (i >= 6) mbar_wait(bar(B_WEMPTY + buf), w_phase(i) ^ 1);
          const int head = 4 * g + 2 * (c ^ w_peer(i)) + ((i >> 1) & 1);
          TR(0, 16 + i);
          mbar_expect_tx(bar(B_WFULL + buf), 16384);
          tma_3d(sb + w_off(buf), &p.wo[r], head * 128 + (i & 1) * 64, 4 * c + 2 * (i >> 3), bar(B_WFULL + buf));
        }
        mbar_wait(bar(B_ZERO_OK), 0);
#pragma unroll 1
        for (int w = 0; w < 2; w++) {
          mbar_wait(bar(B_STAGE_READY + w), 0);
          tma_red_3d(&p.out, (2 * bp + w) * 64, r * 8 + c * 4, sb + (w ? 2 : 4) * UNIT);
        }
        asm volatile("cp.async.bulk.commit_group;" ::: "memory");
        asm volatile("cp.async.bulk.wait_group.read 0;" ::: "memory");
      }
    } else if (warp < 3) {
      cluster_wait();
      int slot = 0; uint32_t ph = 0;
#pragma unroll 1
      for (int s = 0; s < NSTEP; s++) {
        mbar_wait(bar(B_FULL + slot), ph);
        bar_sync(NB_PP0 + warp - 1, 288);
        if (++slot == NSLOT) { slot = 0; ph ^= 1; }
      }
    } else {
      const clock_t t_start = clock();
      uint4* z = reinterpret_cast<uint4*>(out + (size_t)(bp * 128 + g * 16) * 1024 + r * 512 + c * 256) + lane;
#pragma unroll
      for (int i = 0; i < 16; i++) z[i * 128] = make_uint4(0, 0, 0, 0);
      asm volatile("fence.proxy.async.global;" ::: "memory");
      __threadfence();
      __syncwarp();
      cluster_wait();
      {
        while ((int)(clock() - t_start) < PF_QW) __nanosleep(40);
        const char* wsrc = p.wq_ptr[r] + (size_t)(256 + 4 * (lane >> 2) + bp) * 8192 + (4 * g + 2 * c) * 256 + (lane & 3) * 128;
        prefetch_l2(p.x_ptr[r] + (size_t)(bp * 128 + (2 * g + c) * 8 + (lane >> 2)) * 1024 + 512 + (lane & 3) * 128);
#pragma unroll
        for (int i = 0; i < 8; i++) prefetch_l2(wsrc + i * 32 * 8192);
      }
      {
        while ((int)(clock() - t_start) < STAGE_AT) __nanosleep(40);
        const char* kv = p.kv_ptr[r][c] + (size_t)(bp * 16 + g) * 2048 * 256;
#pragma unroll 1
        for (int i = lane; i < (STAGE_END - 3) * STAGE_LINES; i += 32) {
          const int n = 3 + i / STAGE_LINES;
          prefetch_l2(kv + (size_t)(n >> 4) * (16384 * 256) + (n & 15) * UNIT + (i % STAGE_LINES) * 128);
        }
      }
      if (lane == 0) {
        unsigned int* cnt = &g_zero_cnt[(r * 4 + bp) * 2 + c];
        const unsigned int target = (atomicAdd(cnt, 1u) & ~7u) + 8u;
        mbar_wait_sleep(bar(B_O1_READY), 0);
        unsigned int v;
        int i = 0;
        do {
          asm volatile("ld.acquire.gpu.global.u32 %0, [%1];" : "=r"(v) : "l"(cnt) : "memory");
          if (++i == SPIN_LIMIT) __trap();
        } while ((int)(v - target) < 0);
        asm volatile("fence.proxy.async.global;" ::: "memory");
        mbar_arrive(bar(B_ZERO_OK));
        mbar_wait_sleep(bar(B_PEER1_FREE), 0);
        dsmem_copy(mapa(sb + 4 * UNIT, c ^ 1), sb + OFF_STASH, UNIT, mapa(bar(B_O1_IN), c ^ 1));
        mbar_wait(bar(B_PEER2_FREE), 0);
#pragma unroll 1
        for (int w = 0; w < 2; w++) {
          mbar_wait(bar(B_O2_READY + w), 0);
          dsmem_copy(mapa(sb + 2 * UNIT + w * 16384, c ^ 1), sb + UNIT + w * 16384, 16384, mapa(bar(B_O2_IN + w), c ^ 1));
        }
      }
    }
  } else {
    asm volatile("setmaxnreg.inc.sync.aligned.u32 240;");
    const int w = (warp >> 2) - 1;
    const int wq = warp & 3;
    const bool leader = (threadIdx.x & 127) == 0;
    float O[64], S[64];
    uint32_t PA[16], PB[16], PH[16], Q[32];
    uint32_t tick0 = 0, tick1 = 0;
    const uint32_t d0 = (sb & 0x3FFFF) >> 4;
    const uint32_t dK = d0 | (1u << 16);
    const uint32_t dN8 = d0 | (512u << 16);
    const uint32_t dN16 = d0 | (1024u << 16);
    const uint32_t tile_row = (16 * wq + (lane & 7) + ((lane >> 3) & 1) * 8) * 128;
    const uint32_t tile_sw = (lane & 7) ^ (lane >> 4);
    if (leader) TR(1 + w, 0);
    if (w == 1) bar_arrive(NB_PP0, 288);

#pragma unroll 1
    for (int t = 0; t < QSTAGES; t++) {
      mbar_wait(bar(B_QFULL + (t & 3)), t >> 2);
      if (t == 0 && leader) TR(1 + w, 1);
      if (leader && t >= 1) TR(1 + w, 8 + t);
      const uint32_t off = (UNIT + (t & 3) * QBUF) >> 4;
      const uint32_t a = dK + off, b = dN8 + off + ((16384 + w * 16384) >> 4);
      if (QORDER && t == 0 && w == 1) bar_sync(NB_QORD, 256);
      wg_fence();
#pragma unroll
      for (int kk = 0; kk < 4; kk++) {
        wgmma_ss_n128<1>(S, mk_desc(a + kk * 2), mk_desc(b + kk * 128), (t | kk) != 0);
        wgmma_ss_n128<1>(O, mk_desc(a + 512 + kk * 2), mk_desc(b + kk * 128), (t | kk) != 0);
      }
      wg_commit();
      if (QORDER && t == 0 && w == 0) bar_arrive(NB_QORD, 256);
      wg_wait<0>();
      fence_regs(S); fence_regs(O);
      if (leader) mbar_arrive(bar(B_QEMPTY + (t & 3)));
    }
    if (leader) TR(1 + w, 2);
    const uint32_t stash = sb + OFF_STASH + w * 16384;
#pragma unroll
    for (int i = 0; i < 32; i++) Q[i] = pack_bf16(S[2 * i], S[2 * i + 1]);
    fence_regs(Q);
    int slot = 0, vslot = 2;

    const float cs = 0.08838834764831845f * 1.4426950408889634f;
    float b0, b1, l0 = 0.f, l1 = 0.f, s0, s1;
    auto issue_qk = [&]() {
      const uint32_t kb = dK + slot * (SLOT >> 4);
#pragma unroll
      for (int kk = 0; kk < 8; kk++)
        wgmma_rs_n128<0>(S, Q[4 * kk], Q[4 * kk + 1], Q[4 * kk + 2], Q[4 * kk + 3], mk_desc(kb + (kk >> 2) * 1024 + (kk & 3) * 2), kk > 0);
    };
    auto issue_pv = [&](uint32_t (&lo)[16], int acc) {
      const uint32_t vb = dN16 + v_unit(vslot) * (UNIT >> 4);
#pragma unroll
      for (int kk = 0; kk < 4; kk++)
        wgmma_rs_n128<1>(O, lo[4 * kk], lo[4 * kk + 1], lo[4 * kk + 2], lo[4 * kk + 3], mk_desc(vb + kk * 128), kk > 0 ? 1 : acc);
#pragma unroll
      for (int kk = 0; kk < 4; kk++)
        wgmma_rs_n128<1>(O, PH[4 * kk], PH[4 * kk + 1], PH[4 * kk + 2], PH[4 * kk + 3], mk_desc(vb + 512 + kk * 128), 1);
    };
    auto finish_step = [&](uint32_t (&lo)[16]) {
      wg_wait<0>();
      fence_regs(S); fence_regs(O); fence_regs(lo); fence_regs(PH); fence_regs(Q);
      if (leader) mbar_arrive(bar(B_EMPTY + slot));
      vslot = slot;
      if (++slot == NSLOT) slot = 0;
    };
    auto expo = [&](uint32_t (&dst)[16], auto half) {
      constexpr int H = decltype(half)::value;
#pragma unroll
      for (int i = 0; i < 32; i += 4) {
        const float e0 = ex2(fmaf(S[32 * H + i], cs, b0)), e1 = ex2(fmaf(S[32 * H + i + 1], cs, b0));
        const float e2 = ex2(fmaf(S[32 * H + i + 2], cs, b1)), e3 = ex2(fmaf(S[32 * H + i + 3], cs, b1));
        if (i || H) { s0 += e0; s1 += e2; } else { s0 = e0; s1 = e2; }
        s0 += e1; s1 += e3;
        dst[i / 2] = pack_bf16(e0, e1); dst[i / 2 + 1] = pack_bf16(e2, e3);
      }
    };
    constexpr std::integral_constant<int, 0> LO{};
    constexpr std::integral_constant<int, 1> HI{};
    auto tile_max = [&](float& n0, float& n1) {
      float p0 = fmaxf(S[0], S[1]), p1 = fmaxf(S[2], S[3]), q0 = fmaxf(S[4], S[5]), q1 = fmaxf(S[6], S[7]);
#pragma unroll
      for (int i = 8; i < 64; i += 8) {
        p0 = fmaxf(p0, fmaxf(S[i], S[i + 1])); p1 = fmaxf(p1, fmaxf(S[i + 2], S[i + 3]));
        q0 = fmaxf(q0, fmaxf(S[i + 4], S[i + 5])); q1 = fmaxf(q1, fmaxf(S[i + 6], S[i + 7]));
      }
      n0 = fmaxf(p0, q0); n1 = fmaxf(p1, q1);
      n0 = fmaxf(n0, __shfl_xor_sync(~0u, n0, 1)); n1 = fmaxf(n1, __shfl_xor_sync(~0u, n1, 1));
      n0 = fmaxf(n0, __shfl_xor_sync(~0u, n0, 2)); n1 = fmaxf(n1, __shfl_xor_sync(~0u, n1, 2));
      n0 *= -cs; n1 *= -cs;
    };
    auto row_norms = [&](float& r0, float& r1) {
      l0 += __shfl_xor_sync(~0u, l0, 1); l1 += __shfl_xor_sync(~0u, l1, 1);
      l0 += __shfl_xor_sync(~0u, l0, 2); l1 += __shfl_xor_sync(~0u, l1, 2);
      r0 = __fdividef(1.f, l0); r1 = __fdividef(1.f, l1);
    };

    auto finish_softmax = [&](uint32_t (&make)[16], bool guard) {
      expo(PH, HI);
      if (__any_sync(~0u, guard && !(s0 + s1 <= SUM_LIMIT))) {
        float n0, n1;
        tile_max(n0, n1);
        n0 = fminf(n0, b0); n1 = fminf(n1, b1);
        const float a0 = ex2(n0 - b0), a1 = ex2(n1 - b1);
        b0 = n0; b1 = n1; l0 *= a0; l1 *= a1;
#pragma unroll
        for (int i = 0; i < 64; i += 4) { O[i] *= a0; O[i + 1] *= a0; O[i + 2] *= a1; O[i + 3] *= a1; }
        expo(make, LO); expo(PH, HI);
      }
      l0 += s0; l1 += s1;
      fence_regs(make); fence_regs(PH); fence_regs(O);
    };
    float r0 = 1.f, r1 = 1.f;

    bar_sync(NB_PP0 + w, 288);
    wg_fence(); issue_qk(); wg_commit();
    bar_arrive(NB_PP0 + 1 - w, 288);
    cluster_wait();
    finish_step(PB);
    if (leader) TR(1 + w, 3);
    tile_max(b0, b1);
    expo(PA, LO); expo(PH, HI);
    l0 = s0; l1 = s1;
    fence_regs(PA); fence_regs(PH);
    mbar_wait(bar(B_QEMPTY + 3), 1);

#pragma unroll 1
    for (int it = 0;; it++) {
      bar_sync(NB_PP0 + w, 288);
      wg_fence(); issue_qk(); wg_commit();
      if ((it & 7) == 0) {
        store_tile(O, r0, r1, stash + tile_row, tile_sw);
        fence_async_smem();
        if (it) mbar_arrive(bar(B_O1_READY));
        if (it && leader) TR(1 + w, 4);
      }
      fence_regs(O);
      wg_fence(); issue_pv(PA, it & 7); wg_commit();
      bar_arrive(NB_PP0 + 1 - w, 288);
      wg_wait<1>();
      fence_regs(S);
      expo(PB, LO);
      fence_regs(PB);
      asm volatile("mov.u32 %0, %%clock;" : "=r"(tick0) :: "memory");
      finish_step(PA);
      finish_softmax(PB, true);
      if (it == 15) break;

      if (it == 7) {
#pragma unroll
        for (int kk = 0; kk < 8; kk++)
          asm volatile("ldmatrix.sync.aligned.m8n8.x4.shared.b16 {%0, %1, %2, %3}, [%4];"
                       : "=r"(Q[4 * kk]), "=r"(Q[4 * kk + 1]), "=r"(Q[4 * kk + 2]), "=r"(Q[4 * kk + 3])
                       : "r"(stash + tile_row + (kk >> 2) * 8192 + ((((2 * kk) & 7) ^ tile_sw) << 4)) : "memory");
      }
      fence_regs(Q);
      bar_sync(NB_PP0 + w, 288);
      wg_fence(); issue_qk(); wg_commit(); issue_pv(PB, 1); wg_commit();
      bar_arrive(NB_PP0 + 1 - w, 288);
      if (it == 7) { row_norms(r0, r1); l0 = 0.f; l1 = 0.f; }
      wg_wait<1>();
      fence_regs(S);
      if (it == 7) tile_max(b0, b1);
      expo(PA, LO);
      fence_regs(PA);
      asm volatile("mov.u32 %0, %%clock;" : "=r"(tick1) :: "memory");
      finish_step(PB);
      finish_softmax(PA, it != 7);
    }
    bar_sync(NB_PP0 + w, 288);
    wg_fence(); issue_pv(PB, 1); wg_commit();
    if (w == 0) bar_arrive(NB_PP0 + 1, 288);
    {
      row_norms(r0, r1);
      mbar_wait(bar(B_EMPTY + 1), 0);
      finish_step(PB);
      if (leader) TR(1 + w, 5);
      store_tile(O, r0, r1, sb + UNIT + w * 16384 + tile_row, tile_sw);
    }
    fence_async_smem();
    mbar_arrive(bar(B_O2_READY + w));

    if (w == 1) { mbar_wait(bar(B_O2_READY), 0); mbar_wait(bar(B_O2_READY + 1), 0); }
    const uint32_t a_own = dK + ((w ? UNIT : OFF_STASH) >> 4), a_peer = dK + ((w ? 2 * UNIT : 4 * UNIT) >> 4);
    auto oproj_issue = [&](float (&acc)[64], int i) {
      const int buf = w_buf(i);
      if (leader) TR(1 + w, 32 + i);
      mbar_wait(bar(B_WFULL + buf), w_phase(i));
      if (leader) TR(1 + w, 16 + i);
      const uint32_t a = (w_peer(i) ? a_peer : a_own) + (i & 3) * 512, b = dN8 + (w_off(buf) >> 4);
      wg_fence();
#pragma unroll
      for (int kk = 0; kk < 4; kk++) wgmma_ss_n128<1>(acc, mk_desc(a + kk * 2), mk_desc(b + kk * 128), ((i & 7) | kk) != 0);
      wg_commit();
    };
    auto oproj_retire = [&](int i) {
      wg_wait<1>();
      if (leader) mbar_arrive(bar(B_WEMPTY + w_buf(i)));
    };
    oproj_issue(S, 0);
#pragma unroll 1
    for (int i = 1; i < 8; i++) {
      if (i == 4) mbar_wait(bar(w ? B_O2_IN : B_O1_IN), 0);
      if (i == 6 && w) mbar_wait(bar(B_O2_IN + 1), 0);
      oproj_issue(S, i);
      oproj_retire(i - 1);
    }
    cluster_arrive();
    oproj_issue(O, 8); oproj_retire(7);
    fence_regs(S);
    if (leader) TR(1 + w, 6);
    oproj_issue(O, 9); oproj_retire(8);
    const uint32_t stage1 = sb + (w ? 2 : 4) * UNIT + 16384;
    const uint32_t stage0 = stage1 - 16384 + tile_row;
    oproj_issue(O, 10); oproj_retire(9);
    oproj_issue(O, 11);
    store_tile(S, 1.f, 1.f, stage0, tile_sw);
    fence_async_smem();
    mbar_arrive(bar(B_STAGE_READY + w));
    if (OGO && w == 1) bar_sync(NB_QORD, 256);
#pragma unroll 1
    for (int i = 12; i < 16; i++) {
      wg_wait<1>();
      oproj_issue(O, i);
      if (i == OGO && w == 0) bar_arrive(NB_QORD, 256);
    }
    wg_wait<0>();
    fence_regs(O);
    if (leader) TR(1 + w, 7);
    store_tile(O, 1.f, 1.f, stage1 + tile_row, tile_sw);
    fence_async_smem();
    bar_sync(NB_WG0 + w, 128);
    if (leader) {
      mbar_wait(bar(B_ZERO_OK), 0);
      tma_red_3d(&p.out, (2 * bp + w) * 64, r * 8 + c * 4 + 2, stage1);
      asm volatile("cp.async.bulk.commit_group;" ::: "memory");
      asm volatile("cp.async.bulk.wait_group.read 0;" ::: "memory");
      TR(1 + w, 8);
    }
    __syncwarp();
    if (tick0 == tick1 && blockDim.x == 0) out[0] = __float2bfloat16(0.f);
    cluster_wait();
  }
}

typedef CUresult (*EncodeFn)(CUtensorMap*, CUtensorMapDataType, cuuint32_t, void*, const cuuint64_t*, const cuuint64_t*,
                             const cuuint32_t*, const cuuint32_t*, CUtensorMapInterleave, CUtensorMapSwizzle,
                             CUtensorMapL2promotion, CUtensorMapFloatOOBfill);

void encode_3d(EncodeFn fn, CUtensorMap* m, const void* ptr, uint64_t rows, uint64_t cols, uint32_t box_rows, uint32_t groups) {
  cuuint64_t dims[3] = {64, rows, cols / 64};
  cuuint64_t strides[2] = {cols * 2, 128};
  cuuint32_t box[3] = {64, box_rows, groups};
  cuuint32_t es[3] = {1, 1, 1};
  fn(m, CU_TENSOR_MAP_DATA_TYPE_BFLOAT16, 3, const_cast<void*>(ptr), dims, strides, box, es, CU_TENSOR_MAP_INTERLEAVE_NONE,
     CU_TENSOR_MAP_SWIZZLE_128B, CU_TENSOR_MAP_L2_PROMOTION_L2_128B, CU_TENSOR_MAP_FLOAT_OOB_FILL_NONE);
}
void encode_2d(EncodeFn fn, CUtensorMap* m, const void* ptr, uint64_t rows, uint64_t cols, uint32_t box_rows) {
  cuuint64_t dims[2] = {cols, rows};
  cuuint64_t strides[1] = {cols * 2};
  cuuint32_t box[2] = {64, box_rows};
  cuuint32_t es[2] = {1, 1};
  fn(m, CU_TENSOR_MAP_DATA_TYPE_BFLOAT16, 2, const_cast<void*>(ptr), dims, strides, box, es, CU_TENSOR_MAP_INTERLEAVE_NONE,
     CU_TENSOR_MAP_SWIZZLE_128B, CU_TENSOR_MAP_L2_PROMOTION_L2_128B, CU_TENSOR_MAP_FLOAT_OOB_FILL_NONE);
}

}

extern "C" void kernel_launch(void* const* d_in, const int* in_sizes, int n_in, void* d_out, int out_size) {
  (void)in_sizes; (void)n_in; (void)out_size;
  static EncodeFn encode = nullptr;
  if (!encode) {
    void* fn = nullptr;
    cudaDriverEntryPointQueryResult q;
    cudaGetDriverEntryPoint("cuTensorMapEncodeTiled", &fn, cudaEnableDefault, &q);
    encode = (EncodeFn)fn;
    cudaFuncSetAttribute(gqa_fused_kernel, cudaFuncAttributeMaxDynamicSharedMemorySize, SMEM_BYTES);
  }
  Params p;
  for (int r = 0; r < 2; r++) {
    void* const* in = d_in + 5 * r;
    encode_2d(encode, &p.x[r], in[0], 512, 512, 128);
    encode_3d(encode, &p.k[r], in[1], 131072, 128, 128, 2);
    encode_3d(encode, &p.v[r], in[2], 131072, 128, 128, 2);
    encode_3d(encode, &p.wq[r], in[3], 512, 4096, 64, 4);
    encode_3d(encode, &p.wo[r], in[4], 4096, 512, 64, 2);
  }
  for (int r = 0; r < 2; r++) {
    p.x_ptr[r] = (const char*)d_in[5 * r];
    p.kv_ptr[r][0] = (const char*)d_in[5 * r + 1];
    p.kv_ptr[r][1] = (const char*)d_in[5 * r + 2];
    p.wq_ptr[r] = (const char*)d_in[5 * r + 3];
    p.wo_ptr[r] = (const char*)d_in[5 * r + 4];
  }
  encode_3d(encode, &p.out, d_out, 512, 1024, 64, 2);
  gqa_fused_kernel<<<128, 384, SMEM_BYTES, cudaStreamPerThread>>>(p, (__nv_bfloat16*)d_out);
}
```

```cpp
#include <cuda_runtime.h>
#include <cuda.h>
#include <cuda_bf16.h>
#include <stdint.h>
#include <type_traits>

namespace {

constexpr int UNIT = 32768;
constexpr int SLOT = 2 * UNIT;
constexpr int NSLOT = 3;
constexpr int OFF_STASH = 5 * UNIT;
constexpr int OFF_BAR = 7 * UNIT;
constexpr int SMEM_BYTES = OFF_BAR + 512 + 1024;
constexpr int QSTAGES = 8;
constexpr int QBUF = 49152;
constexpr int NSTEP = 33;
constexpr int EARLYQ = 2;
constexpr int STAGE_LINES = 8;
constexpr int STAGE_AT = 2500;
constexpr int STAGE_GAP = 900;
constexpr int XPIECE = 4096;
constexpr float SUM_LIMIT = 4096.f;
constexpr int SPIN_LIMIT = 1 << 22;

enum { B_FULL = 0, B_EMPTY = 3, B_QFULL = 6, B_QEMPTY = 10, B_WFULL = 14, B_WEMPTY = 20, B_O1_READY = 26, B_O2_READY = 27,
       B_STAGE_READY = 29, B_PEER1_FREE = 31, B_PEER2_FREE = 32, B_O1_IN = 33, B_O2_IN = 34, B_ZERO_OK = 36,
       B_PEER_GOT = 37 };
enum { NB_PP0 = 1, NB_WG0 = 3, NB_ORDER = 5 };

__device__ __forceinline__ uint32_t v_unit(int slot) { return slot == 2 ? 6 : 2 * slot + 1; }
__device__ __forceinline__ int w_buf(int i) { return i < 6 ? i : i < 12 ? i - 6 : i - 12; }
__device__ __forceinline__ uint32_t w_phase(int i) { return i >= 6 && i < 12; }
__device__ __forceinline__ int w_peer(int i) { return ((i + 4) >> 3) & 1; }
__device__ __forceinline__ uint32_t w_off(int buf) { return (buf < 2 ? 0 : buf < 4 ? 6 * UNIT : 3 * UNIT) + (buf & 1) * 16384; }

struct Params {
  CUtensorMap x[2], wq[2], k[2], v[2], wo[2], out;
  const char* kv_ptr[2][2];
  const char *x_ptr[2], *wq_ptr[2];
};

__device__ unsigned int g_ticket[16], g_cleared[16];

__device__ __forceinline__ uint32_t smem_u32(const void* p) { return (uint32_t)__cvta_generic_to_shared(p); }
__device__ __forceinline__ void mbar_init(uint32_t bar, uint32_t cnt) { asm volatile("mbarrier.init.shared::cta.b64 [%0], %1;" :: "r"(bar), "r"(cnt)); }
__device__ __forceinline__ void mbar_expect_tx(uint32_t bar, uint32_t bytes) { asm volatile("mbarrier.arrive.expect_tx.shared::cta.b64 _, [%0], %1;" :: "r"(bar), "r"(bytes) : "memory"); }
__device__ __forceinline__ void mbar_arrive(uint32_t bar) { asm volatile("mbarrier.arrive.shared::cta.b64 _, [%0];" :: "r"(bar) : "memory"); }
__device__ __forceinline__ uint32_t mapa(uint32_t addr, uint32_t cta) { uint32_t r; asm("mapa.shared::cluster.u32 %0, %1, %2;" : "=r"(r) : "r"(addr), "r"(cta)); return r; }
__device__ __forceinline__ void mbar_arrive_remote(uint32_t rbar) { asm volatile("mbarrier.arrive.shared::cluster.b64 _, [%0];" :: "r"(rbar) : "memory"); }
__device__ __forceinline__ bool mbar_try(uint32_t bar, uint32_t parity) {
  uint32_t ok;
  asm volatile("{ .reg .pred p; mbarrier.try_wait.parity.shared::cta.b64 p, [%1], %2; selp.u32 %0, 1, 0, p; }" : "=r"(ok) : "r"(bar), "r"(parity) : "memory");
  return ok;
}
__device__ __forceinline__ void mbar_wait(uint32_t bar, uint32_t parity) {
  if (mbar_try(bar, parity)) return;
#pragma unroll 1
  for (int i = 0; i < SPIN_LIMIT; i++) if (mbar_try(bar, parity)) return;
  __trap();
}
__device__ __forceinline__ void mbar_wait_sleep(uint32_t bar, uint32_t parity) {
#pragma unroll 1
  for (int i = 0; i < SPIN_LIMIT; i++) { if (mbar_try(bar, parity)) return; __nanosleep(200); }
  __trap();
}
__device__ __forceinline__ void tma_2d(uint32_t dst, const CUtensorMap* m, int c0, int c1, uint32_t bar) {
  asm volatile("cp.async.bulk.tensor.2d.shared::cluster.global.mbarrier::complete_tx::bytes [%0], [%1, {%3, %4}], [%2];"
    :: "r"(dst), "l"(m), "r"(bar), "r"(c0), "r"(c1) : "memory");
}
__device__ __forceinline__ void tma_3d(uint32_t dst, const CUtensorMap* m, int c1, int c2, uint32_t bar) {
  asm volatile("cp.async.bulk.tensor.3d.shared::cluster.global.mbarrier::complete_tx::bytes [%0], [%1, {%3, %4, %5}], [%2];"
    :: "r"(dst), "l"(m), "r"(bar), "r"(0), "r"(c1), "r"(c2) : "memory");
}
__device__ __forceinline__ void tma_3d_hint(uint32_t dst, const CUtensorMap* m, int c1, int c2, uint32_t bar, uint64_t pol) {
  asm volatile("cp.async.bulk.tensor.3d.shared::cluster.global.mbarrier::complete_tx::bytes.L2::cache_hint [%0], [%1, {%3, %4, %5}], [%2], %6;"
    :: "r"(dst), "l"(m), "r"(bar), "r"(0), "r"(c1), "r"(c2), "l"(pol) : "memory");
}
__device__ __forceinline__ void tma_red_3d(const CUtensorMap* m, int c1, int c2, uint32_t src) {
  asm volatile("cp.reduce.async.bulk.tensor.3d.global.shared::cta.add.tile.bulk_group [%0, {%2, %3, %4}], [%1];"
    :: "l"(m), "r"(src), "r"(0), "r"(c1), "r"(c2) : "memory");
}
__device__ __forceinline__ void dsmem_copy(uint32_t rdst, uint32_t src, uint32_t bytes, uint32_t rbar) {
  asm volatile("cp.async.bulk.shared::cluster.shared::cta.mbarrier::complete_tx::bytes [%0], [%1], %2, [%3];"
    :: "r"(rdst), "r"(src), "r"(bytes), "r"(rbar) : "memory");
}
__device__ __forceinline__ void prefetch_map(const CUtensorMap* m) { asm volatile("prefetch.tensormap [%0];" :: "l"(m) : "memory"); }
__device__ __forceinline__ void prefetch_l2(const char* p) { asm volatile("prefetch.global.L2 [%0];" :: "l"(p) : "memory"); }
__device__ __forceinline__ void fence_async_smem() { asm volatile("fence.proxy.async.shared::cta;" ::: "memory"); }
__device__ __forceinline__ void bar_sync(int id, int n) { asm volatile("barrier.cta.sync %0, %1;" :: "r"(id), "r"(n) : "memory"); }
__device__ __forceinline__ void bar_arrive(int id, int n) { asm volatile("barrier.cta.arrive %0, %1;" :: "r"(id), "r"(n) : "memory"); }
__device__ __forceinline__ void cluster_arrive() { asm volatile("barrier.cluster.arrive.relaxed.aligned;" ::: "memory"); }
__device__ __forceinline__ void cluster_wait() { asm volatile("barrier.cluster.wait.aligned;" ::: "memory"); }
__device__ __forceinline__ void sched_fence() { asm volatile("pmevent 0;" ::: "memory"); }
__device__ __forceinline__ void wg_fence() { asm volatile("wgmma.fence.sync.aligned;" ::: "memory"); }
__device__ __forceinline__ void wg_commit() { asm volatile("wgmma.commit_group.sync.aligned;" ::: "memory"); }
template <int N> __device__ __forceinline__ void wg_wait() { asm volatile("wgmma.wait_group.sync.aligned %0;" :: "n"(N) : "memory"); }
template <int N> __device__ __forceinline__ void fence_regs(float (&d)[N]) {
#pragma unroll
  for (int i = 0; i < N; i++) asm volatile("" : "+f"(d[i]) :: "memory");
}
template <int N> __device__ __forceinline__ void fence_regs(uint32_t (&d)[N]) {
#pragma unroll
  for (int i = 0; i < N; i++) asm volatile("" : "+r"(d[i]) :: "memory");
}
__device__ __forceinline__ uint64_t mk_desc(uint32_t lo) { return ((uint64_t)0x40000040u << 32) | lo; }
__device__ __forceinline__ float ex2(float x) { float y; asm("ex2.approx.ftz.f32 %0, %1;" : "=f"(y) : "f"(x)); return y; }
__device__ __forceinline__ uint32_t pack_bf16(float lo, float hi) { uint32_t r; asm("cvt.rn.bf16x2.f32 %0, %1, %2;" : "=r"(r) : "f"(hi), "f"(lo)); return r; }
__device__ __forceinline__ void stsm4(uint32_t addr, uint32_t a, uint32_t b, uint32_t c, uint32_t d) {
  asm volatile("stmatrix.sync.aligned.m8n8.x4.shared.b16 [%0], {%1, %2, %3, %4};" :: "r"(addr), "r"(a), "r"(b), "r"(c), "r"(d) : "memory");
}

template <int TB>
__device__ __forceinline__ void wgmma_ss_n128(float (&d)[64], uint64_t da, uint64_t db, int acc) {
  asm volatile("{ .reg .pred p; setp.ne.b32 p, %66, 0;\n"
    "wgmma.mma_async.sync.aligned.m64n128k16.f32.bf16.bf16 {"
    "%0, %1, %2, %3, %4, %5, %6, %7, %8, %9, %10, %11, %12, %13, %14, %15,"
    "%16, %17, %18, %19, %20, %21, %22, %23, %24, %25, %26, %27, %28, %29, %30, %31,"
    "%32, %33, %34, %35, %36, %37, %38, %39, %40, %41, %42, %43, %44, %45, %46, %47,"
    "%48, %49, %50, %51, %52, %53, %54, %55, %56, %57, %58, %59, %60, %61, %62, %63"
    "}, %64, %65, p, 1, 1, 0, %67; }"
    : "+f"(d[0]), "+f"(d[1]), "+f"(d[2]), "+f"(d[3]), "+f"(d[4]), "+f"(d[5]), "+f"(d[6]), "+f"(d[7]),
      "+f"(d[8]), "+f"(d[9]), "+f"(d[10]), "+f"(d[11]), "+f"(d[12]), "+f"(d[13]), "+f"(d[14]), "+f"(d[15]),
      "+f"(d[16]), "+f"(d[17]), "+f"(d[18]), "+f"(d[19]), "+f"(d[20]), "+f"(d[21]), "+f"(d[22]), "+f"(d[23]),
      "+f"(d[24]), "+f"(d[25]), "+f"(d[26]), "+f"(d[27]), "+f"(d[28]), "+f"(d[29]), "+f"(d[30]), "+f"(d[31]),
      "+f"(d[32]), "+f"(d[33]), "+f"(d[34]), "+f"(d[35]), "+f"(d[36]), "+f"(d[37]), "+f"(d[38]), "+f"(d[39]),
      "+f"(d[40]), "+f"(d[41]), "+f"(d[42]), "+f"(d[43]), "+f"(d[44]), "+f"(d[45]), "+f"(d[46]), "+f"(d[47]),
      "+f"(d[48]), "+f"(d[49]), "+f"(d[50]), "+f"(d[51]), "+f"(d[52]), "+f"(d[53]), "+f"(d[54]), "+f"(d[55]),
      "+f"(d[56]), "+f"(d[57]), "+f"(d[58]), "+f"(d[59]), "+f"(d[60]), "+f"(d[61]), "+f"(d[62]), "+f"(d[63])
    : "l"(da), "l"(db), "r"(acc), "n"(TB));
}
template <int TB>
__device__ __forceinline__ void wgmma_rs_n128(float (&d)[64], uint32_t a0, uint32_t a1, uint32_t a2, uint32_t a3, uint64_t db, int acc) {
  asm volatile("{ .reg .pred p; setp.ne.b32 p, %69, 0;\n"
    "wgmma.mma_async.sync.aligned.m64n128k16.f32.bf16.bf16 {"
    "%0, %1, %2, %3, %4, %5, %6, %7, %8, %9, %10, %11, %12, %13, %14, %15,"
    "%16, %17, %18, %19, %20, %21, %22, %23, %24, %25, %26, %27, %28, %29, %30, %31,"
    "%32, %33, %34, %35, %36, %37, %38, %39, %40, %41, %42, %43, %44, %45, %46, %47,"
    "%48, %49, %50, %51, %52, %53, %54, %55, %56, %57, %58, %59, %60, %61, %62, %63"
    "}, {%64, %65, %66, %67}, %68, p, 1, 1, %70; }"
    : "+f"(d[0]), "+f"(d[1]), "+f"(d[2]), "+f"(d[3]), "+f"(d[4]), "+f"(d[5]), "+f"(d[6]), "+f"(d[7]),
      "+f"(d[8]), "+f"(d[9]), "+f"(d[10]), "+f"(d[11]), "+f"(d[12]), "+f"(d[13]), "+f"(d[14]), "+f"(d[15]),
      "+f"(d[16]), "+f"(d[17]), "+f"(d[18]), "+f"(d[19]), "+f"(d[20]), "+f"(d[21]), "+f"(d[22]), "+f"(d[23]),
      "+f"(d[24]), "+f"(d[25]), "+f"(d[26]), "+f"(d[27]), "+f"(d[28]), "+f"(d[29]), "+f"(d[30]), "+f"(d[31]),
      "+f"(d[32]), "+f"(d[33]), "+f"(d[34]), "+f"(d[35]), "+f"(d[36]), "+f"(d[37]), "+f"(d[38]), "+f"(d[39]),
      "+f"(d[40]), "+f"(d[41]), "+f"(d[42]), "+f"(d[43]), "+f"(d[44]), "+f"(d[45]), "+f"(d[46]), "+f"(d[47]),
      "+f"(d[48]), "+f"(d[49]), "+f"(d[50]), "+f"(d[51]), "+f"(d[52]), "+f"(d[53]), "+f"(d[54]), "+f"(d[55]),
      "+f"(d[56]), "+f"(d[57]), "+f"(d[58]), "+f"(d[59]), "+f"(d[60]), "+f"(d[61]), "+f"(d[62]), "+f"(d[63])
    : "r"(a0), "r"(a1), "r"(a2), "r"(a3), "l"(db), "r"(acc), "n"(TB));
}

template <int K0 = 0, int K1 = 8>
__device__ __forceinline__ void store_tile(const float (&a)[64], float r0, float r1, uint32_t row_addr, uint32_t sw) {
#pragma unroll
  for (int kk = K0; kk < K1; kk++) {
    uint32_t chunk = ((2 * kk) & 7) ^ sw;
    stsm4(row_addr + (kk >> 2) * 8192 + chunk * 16,
          pack_bf16(a[8 * kk] * r0, a[8 * kk + 1] * r0), pack_bf16(a[8 * kk + 2] * r1, a[8 * kk + 3] * r1),
          pack_bf16(a[8 * kk + 4] * r0, a[8 * kk + 5] * r0), pack_bf16(a[8 * kk + 6] * r1, a[8 * kk + 7] * r1));
  }
}

template <int K0, int N>
__device__ __forceinline__ void load_tile(uint32_t (&f)[N], uint32_t row_addr, uint32_t sw) {
#pragma unroll
  for (int i = 0; i < N / 4; i++) {
    const int kk = K0 + i;
    asm volatile("ldmatrix.sync.aligned.m8n8.x4.shared.b16 {%0, %1, %2, %3}, [%4];"
                 : "=r"(f[4 * i]), "=r"(f[4 * i + 1]), "=r"(f[4 * i + 2]), "=r"(f[4 * i + 3])
                 : "r"(row_addr + (kk >> 2) * 8192 + ((((2 * kk) & 7) ^ sw) << 4)) : "memory");
  }
}

__global__ void __cluster_dims__(2, 1, 1) __launch_bounds__(384, 1)
gqa_fused_kernel(const __grid_constant__ Params p, __nv_bfloat16* __restrict__ out) {
  extern __shared__ __align__(1024) char smem_raw[];
  const uint32_t sb = (smem_u32(smem_raw) + 1023u) & ~1023u;
  const uint32_t bars = sb + OFF_BAR;
  auto bar = [&](int i) { return bars + 8u * i; };

  const int c = blockIdx.x & 1, u = blockIdx.x >> 1;
  int r, g, bp;
  if (u < 4) { r = 1; g = 7; bp = u; }
  else if (u < 36) { const int i = (u - 4) & 7; bp = (u - 4) >> 3; r = i >> 2; g = i & 3; }
  else { bp = (u - 36) / 7; const int j = (u - 36) - 7 * bp; r = j >> 2; g = 4 + (j & 3); }
  const int warp = __shfl_sync(~0u, (int)(threadIdx.x >> 5), 0);
  const int lane = threadIdx.x & 31;

  auto load_q = [&](int t) {
    const uint32_t dst = sb + UNIT + (t & 3) * QBUF, fb = bar(B_QFULL + (t & 3));
    mbar_expect_tx(fb, QBUF);
    tma_3d(dst + 16384, &p.wq[r], t * 64, 8 * g + 4 * c, fb);
    tma_2d(dst, &p.x[r], t * 64, bp * 128, fb);
  };
  if (threadIdx.x >= 128) {
    const int tid = threadIdx.x - 128;
    if (tid < 64) prefetch_l2(p.wq_ptr[r] + (size_t)(4 * (tid >> 2) + bp) * 8192 + (4 * g + 2 * c) * 256 + (tid & 3) * 128);
    else if (tid >= 248) prefetch_l2(p.x_ptr[r] + (size_t)(bp * 128 + (2 * g + c) * 8 + (tid & 7)) * 1024);
  }
  if (warp == 1 && lane < 3) prefetch_map(lane == 0 ? &p.wq[r] : lane == 1 ? &p.x[r] : &p.k[r]);
  if (threadIdx.x == 0) {
#pragma unroll
    for (int i = 0; i < 4; i++) mbar_init(bar(B_QFULL + i), 1);
    asm volatile("fence.mbarrier_init.release.cluster;" ::: "memory");
    fence_async_smem();
#pragma unroll 1
    for (int t = 0; t < EARLYQ; t++) load_q(t);
#pragma unroll
    for (int i = 0; i < 4; i++) mbar_init(bar(B_QEMPTY + i), 2);
#pragma unroll
    for (int i = 0; i < NSLOT; i++) { mbar_init(bar(B_FULL + i), 1); mbar_init(bar(B_EMPTY + i), 2); }
#pragma unroll
    for (int i = 0; i < 6; i++) { mbar_init(bar(B_WFULL + i), 1); mbar_init(bar(B_WEMPTY + i), 2); }
    mbar_init(bar(B_O1_READY), 256);
    mbar_init(bar(B_PEER_GOT), 2);
#pragma unroll
    for (int i = B_O2_READY; i < B_PEER1_FREE; i++) mbar_init(bar(i), 128);
#pragma unroll
    for (int i = B_PEER1_FREE; i <= B_ZERO_OK; i++) mbar_init(bar(i), 1);
    asm volatile("fence.mbarrier_init.release.cluster;" ::: "memory");
    mbar_expect_tx(bar(B_O1_IN), UNIT);
    mbar_expect_tx(bar(B_O2_IN), UNIT / 2);
    mbar_expect_tx(bar(B_O2_IN + 1), UNIT / 2);
  }
  __syncthreads();
  cluster_arrive();

  if (warp < 4) {
    asm volatile("setmaxnreg.dec.sync.aligned.u32 24;");
    if (warp == 0) {
      const int row0 = (bp * 16 + g) * 2048;
      uint64_t pol;
      asm volatile("createpolicy.fractional.L2::evict_first.b64 %0, 1.0;" : "=l"(pol));
      auto load_k = [&](int n, int slot) { tma_3d_hint(sb + slot * SLOT, &p.k[r], row0 + (n >> 4) * 16384 + (n & 15) * 128, 0, bar(B_FULL + slot), pol); };
      auto load_v = [&](int n, int vslot, int slot) { tma_3d_hint(sb + v_unit(vslot) * UNIT, &p.v[r], row0 + (n >> 4) * 16384 + (n & 15) * 128, 0, bar(B_FULL + slot), pol); };
      if (lane == 0) {
#pragma unroll 1
        for (int t = EARLYQ; t < 4; t++) load_q(t);
        mbar_expect_tx(bar(B_FULL), UNIT);
        load_k(0, 0);
        prefetch_map(&p.v[r]); prefetch_map(&p.wo[r]); prefetch_map(&p.out);
      }
      __syncwarp();
      cluster_wait();
      if (lane == 0) {
#pragma unroll 1
        for (int t = 4; t < QSTAGES; t++) { mbar_wait(bar(B_QEMPTY + (t & 3)), 0); load_q(t); }
        mbar_expect_tx(bar(B_FULL + 1), SLOT);
        mbar_expect_tx(bar(B_FULL + 2), SLOT);
        mbar_wait(bar(B_QEMPTY + 0), 1);
        load_v(0, 0, 1);
        mbar_wait(bar(B_QEMPTY + 1), 1);
        load_k(1, 1);
        mbar_wait(bar(B_QEMPTY + 2), 1);
        load_v(1, 1, 2);
        mbar_wait(bar(B_QEMPTY + 3), 1);
        load_k(2, 2);
        int slot = 0, vslot = 2; uint32_t ph = 0;
#pragma unroll 1
        for (int s = 3; s < NSTEP; s++) {
          mbar_wait(bar(B_EMPTY + slot), ph);
          mbar_expect_tx(bar(B_FULL + slot), s == NSTEP - 1 ? UNIT : SLOT);
          if (s < NSTEP - 1) load_k(s, slot);
          load_v(s - 1, vslot, slot);
          vslot = slot;
          if (++slot == NSLOT) { slot = 0; ph ^= 1; }
        }
        mbar_arrive_remote(mapa(bar(B_PEER1_FREE), c ^ 1));
        mbar_wait(bar(B_EMPTY + 0), 0);
#pragma unroll 1
        for (int i = 0; i < 16; i++) {
          const int buf = w_buf(i);
          if (i == 4) {
            mbar_wait(bar(B_EMPTY + 1), 0);
            mbar_arrive_remote(mapa(bar(B_PEER2_FREE), c ^ 1));
            mbar_wait(bar(B_EMPTY + 2), 0);
          }
          if (i >= 6) mbar_wait(bar(B_WEMPTY + buf), w_phase(i) ^ 1);
          const int head = 4 * g + 2 * (c ^ w_peer(i)) + ((i >> 1) & 1);
          mbar_expect_tx(bar(B_WFULL + buf), 16384);
          tma_3d(sb + w_off(buf), &p.wo[r], head * 128 + (i & 1) * 64, 4 * c + 2 * (i >> 3), bar(B_WFULL + buf));
        }
        mbar_wait(bar(B_ZERO_OK), 0);
#pragma unroll 1
        for (int w = 0; w < 2; w++) {
          mbar_wait(bar(B_STAGE_READY + w), 0);
          tma_red_3d(&p.out, (2 * bp + w) * 64, r * 8 + c * 4, sb + (w ? 2 : 4) * UNIT);
        }
        asm volatile("cp.async.bulk.commit_group;" ::: "memory");
        asm volatile("cp.async.bulk.wait_group.read 0;" ::: "memory");
      }
    } else if (warp < 3) {
      cluster_wait();
      int slot = 0; uint32_t ph = 0;
#pragma unroll 1
      for (int s = 0; s < NSTEP; s++) {
        mbar_wait(bar(B_FULL + slot), ph);
        bar_sync(NB_PP0 + warp - 1, 288);
        if (++slot == NSLOT) { slot = 0; ph ^= 1; }
      }
    } else {
      const clock_t t_start = clock();
      cluster_wait();
      {
        const char* kv = p.kv_ptr[r][c] + (size_t)(bp * 16 + g) * 2048 * 256;
        int due = STAGE_AT;
#pragma unroll 1
        for (int i0 = 0; i0 < 29 * STAGE_LINES; i0 += 32, due += STAGE_GAP) {
          while ((int)(clock() - t_start) < due) __nanosleep(100);
          const int i = i0 + lane, n = 3 + i / STAGE_LINES;
          if (n < 32) prefetch_l2(kv + (size_t)(n >> 4) * (16384 * 256) + (n & 15) * UNIT + (i % STAGE_LINES) * 128);
        }
      }
      const int grp = (r * 4 + bp) * 2 + c;
      unsigned int ticket = 0;
      if (lane == 0) ticket = atomicAdd(&g_ticket[grp], 1u);
      ticket = __shfl_sync(~0u, ticket, 0);
      const unsigned int epoch = (ticket >> 3) + 1u;
      if ((ticket & 7u) == 0) {
        uint4* z = reinterpret_cast<uint4*>(out + (size_t)bp * 128 * 1024 + r * 512 + c * 256) + lane;
#pragma unroll 1
        for (int i = 0; i < 128; i += 8) {
#pragma unroll
          for (int j = 0; j < 8; j++) z[(i + j) * 128] = make_uint4(0, 0, 0, 0);
          __nanosleep(500);
        }
        asm volatile("fence.proxy.async.global;" ::: "memory");
        __threadfence();
        __syncwarp();
        if (lane == 0) asm volatile("st.release.gpu.global.u32 [%0], %1;" :: "l"(&g_cleared[grp]), "r"(epoch) : "memory");
      }
      if (lane == 0) {
        mbar_wait_sleep(bar(B_O1_READY), 0);
        mbar_wait_sleep(bar(B_PEER1_FREE), 0);
        dsmem_copy(mapa(sb + 4 * UNIT, c ^ 1), sb + OFF_STASH, UNIT, mapa(bar(B_O1_IN), c ^ 1));
        unsigned int v;
        int i = 0;
        do {
          asm volatile("ld.acquire.gpu.global.u32 %0, [%1];" : "=r"(v) : "l"(&g_cleared[grp]) : "memory");
          if (++i == SPIN_LIMIT) __trap();
        } while (v != epoch);
        asm volatile("fence.proxy.async.global;" ::: "memory");
        mbar_arrive(bar(B_ZERO_OK));
        mbar_wait(bar(B_PEER2_FREE), 0);
#pragma unroll 1
        for (int w = 0; w < 2; w++) {
          mbar_wait(bar(B_O2_READY + w), 0);
#pragma unroll 1
          for (int o = 0; o < 16384; o += XPIECE) {
            dsmem_copy(mapa(sb + 2 * UNIT + w * 16384 + o, c ^ 1), sb + UNIT + w * 16384 + o, XPIECE, mapa(bar(B_O2_IN + w), c ^ 1));
            __nanosleep(80);
          }
        }
        mbar_wait(bar(B_PEER_GOT), 0);
      }
    }
  } else {
    asm volatile("setmaxnreg.inc.sync.aligned.u32 240;");
    const int w = (warp >> 2) - 1;
    const int wq = warp & 3;
    const bool leader = (threadIdx.x & 127) == 0;
    float O[64], S[64];
    uint32_t PA[16], PB[16], PH[16], Q[32];
    const uint32_t d0 = (sb & 0x3FFFF) >> 4;
    const uint32_t dK = d0 | (1u << 16);
    const uint32_t dN8 = d0 | (512u << 16);
    const uint32_t dN16 = d0 | (1024u << 16);
    const uint32_t tile_row = (16 * wq + (lane & 7) + ((lane >> 3) & 1) * 8) * 128;
    const uint32_t tile_sw = (lane & 7) ^ (lane >> 4);
    if (w == 1) bar_arrive(NB_PP0, 288);

#pragma unroll 1
    for (int t = 0; t < QSTAGES; t++) {
      mbar_wait(bar(B_QFULL + (t & 3)), t >> 2);
      const uint32_t off = (UNIT + (t & 3) * QBUF) >> 4;
      const uint32_t a = dK + off, b = dN8 + off + ((16384 + w * 16384) >> 4);
      if (t == 0 && w == 1) bar_sync(NB_ORDER, 256);
      wg_fence();
#pragma unroll
      for (int kk = 0; kk < 4; kk++) {
        wgmma_ss_n128<1>(S, mk_desc(a + kk * 2), mk_desc(b + kk * 128), (t | kk) != 0);
        wgmma_ss_n128<1>(O, mk_desc(a + 512 + kk * 2), mk_desc(b + kk * 128), (t | kk) != 0);
      }
      wg_commit();
      if (t == 0 && w == 0) bar_arrive(NB_ORDER, 256);
      wg_wait<0>();
      fence_regs(S); fence_regs(O);
      if (leader) mbar_arrive(bar(B_QEMPTY + (t & 3)));
    }
    const uint32_t stash = sb + OFF_STASH + w * 16384;
#pragma unroll
    for (int i = 0; i < 32; i++) Q[i] = pack_bf16(S[2 * i], S[2 * i + 1]);
    fence_regs(Q);
    int slot = 0, vslot = 2;

    const float cs = 0.08838834764831845f * 1.4426950408889634f;
    float b0, b1;
    float l0 = 0.f, l1 = 0.f;
    float s0, s1;
    auto issue_qk = [&]() {
      const uint32_t kb = dK + slot * (SLOT >> 4);
#pragma unroll
      for (int kk = 0; kk < 8; kk++)
        wgmma_rs_n128<0>(S, Q[4 * kk], Q[4 * kk + 1], Q[4 * kk + 2], Q[4 * kk + 3], mk_desc(kb + (kk >> 2) * 1024 + (kk & 3) * 2), kk > 0);
    };
    auto issue_pv = [&](uint32_t (&lo)[16], int acc) {
      const uint32_t vb = dN16 + v_unit(vslot) * (UNIT >> 4);
#pragma unroll
      for (int kk = 0; kk < 4; kk++)
        wgmma_rs_n128<1>(O, lo[4 * kk], lo[4 * kk + 1], lo[4 * kk + 2], lo[4 * kk + 3], mk_desc(vb + kk * 128), kk > 0 ? 1 : acc);
#pragma unroll
      for (int kk = 0; kk < 4; kk++)
        wgmma_rs_n128<1>(O, PH[4 * kk], PH[4 * kk + 1], PH[4 * kk + 2], PH[4 * kk + 3], mk_desc(vb + 512 + kk * 128), 1);
    };
    auto finish_step = [&](uint32_t (&lo)[16]) {
      wg_wait<0>();
      fence_regs(S); fence_regs(O); fence_regs(lo); fence_regs(PH); fence_regs(Q);
      if (leader) mbar_arrive(bar(B_EMPTY + slot));
      vslot = slot;
      if (++slot == NSLOT) slot = 0;
    };
    auto expo = [&](uint32_t (&dst)[16], auto half) {
      constexpr int H = decltype(half)::value;
#pragma unroll
      for (int i = 0; i < 32; i += 4) {
        const float e0 = ex2(fmaf(S[32 * H + i], cs, b0)), e1 = ex2(fmaf(S[32 * H + i + 1], cs, b0));
        const float e2 = ex2(fmaf(S[32 * H + i + 2], cs, b1)), e3 = ex2(fmaf(S[32 * H + i + 3], cs, b1));
        if (i || H) { s0 += e0; s1 += e2; } else { s0 = e0; s1 = e2; }
        s0 += e1; s1 += e3;
        dst[i / 2] = pack_bf16(e0, e1); dst[i / 2 + 1] = pack_bf16(e2, e3);
      }
    };
    constexpr std::integral_constant<int, 0> LO{};
    constexpr std::integral_constant<int, 1> HI{};
    auto tile_max = [&](float& n0, float& n1) {
      float p0 = fmaxf(S[0], S[1]), p1 = fmaxf(S[2], S[3]), q0 = fmaxf(S[4], S[5]), q1 = fmaxf(S[6], S[7]);
#pragma unroll
      for (int i = 8; i < 64; i += 8) {
        p0 = fmaxf(p0, fmaxf(S[i], S[i + 1])); p1 = fmaxf(p1, fmaxf(S[i + 2], S[i + 3]));
        q0 = fmaxf(q0, fmaxf(S[i + 4], S[i + 5])); q1 = fmaxf(q1, fmaxf(S[i + 6], S[i + 7]));
      }
      n0 = fmaxf(p0, q0); n1 = fmaxf(p1, q1);
      n0 = fmaxf(n0, __shfl_xor_sync(~0u, n0, 1)); n1 = fmaxf(n1, __shfl_xor_sync(~0u, n1, 1));
      n0 = fmaxf(n0, __shfl_xor_sync(~0u, n0, 2)); n1 = fmaxf(n1, __shfl_xor_sync(~0u, n1, 2));
      n0 *= -cs; n1 *= -cs;
    };
    auto row_norms = [&](float& r0, float& r1) {
      l0 += __shfl_xor_sync(~0u, l0, 1); l1 += __shfl_xor_sync(~0u, l1, 1);
      l0 += __shfl_xor_sync(~0u, l0, 2); l1 += __shfl_xor_sync(~0u, l1, 2);
      r0 = __fdividef(1.f, l0); r1 = __fdividef(1.f, l1);
    };

    auto finish_softmax = [&](uint32_t (&make)[16], bool guard) {
      expo(PH, HI);
      if (__any_sync(~0u, guard && !(s0 + s1 <= SUM_LIMIT))) {
        float n0, n1;
        tile_max(n0, n1);
        n0 = fminf(n0, b0); n1 = fminf(n1, b1);
        const float a0 = ex2(n0 - b0), a1 = ex2(n1 - b1);
        b0 = n0; b1 = n1; l0 *= a0; l1 *= a1;
#pragma unroll
        for (int i = 0; i < 64; i += 4) { O[i] *= a0; O[i + 1] *= a0; O[i + 2] *= a1; O[i + 3] *= a1; }
        expo(make, LO); expo(PH, HI);
      }
      l0 += s0; l1 += s1;
      fence_regs(make); fence_regs(PH); fence_regs(O);
    };
    float r0 = 1.f, r1 = 1.f;

    bar_sync(NB_PP0 + w, 288);
    wg_fence(); issue_qk(); wg_commit();
    bar_arrive(NB_PP0 + 1 - w, 288);
    cluster_wait();
    finish_step(PB);
    tile_max(b0, b1);
    expo(PA, LO); expo(PH, HI);
    l0 = s0; l1 = s1;
    fence_regs(PA); fence_regs(PH);
    mbar_wait(bar(B_QEMPTY + 3), 1);

#pragma unroll 1
    for (int it = 0;; it++) {
      bar_sync(NB_PP0 + w, 288);
      wg_fence(); issue_qk(); wg_commit();
      if ((it & 7) == 0) store_tile(O, r0, r1, stash + tile_row, tile_sw);
      fence_regs(O);
      wg_fence(); issue_pv(PA, it & 7); wg_commit();
      bar_arrive(NB_PP0 + 1 - w, 288);
      if (it == 8) {
        fence_async_smem();
        mbar_arrive(bar(B_O1_READY));
      }
      wg_wait<1>();
      fence_regs(S);
      expo(PB, LO);
      fence_regs(PB);
      sched_fence();
      finish_step(PA);
      finish_softmax(PB, true);
      if (it == 15) break;

      if (it == 7) load_tile<0>(Q, stash + tile_row, tile_sw);
      fence_regs(Q);
      bar_sync(NB_PP0 + w, 288);
      wg_fence(); issue_qk(); wg_commit(); issue_pv(PB, 1); wg_commit();
      bar_arrive(NB_PP0 + 1 - w, 288);
      if (it == 7) { row_norms(r0, r1); l0 = 0.f; l1 = 0.f; }
      wg_wait<1>();
      fence_regs(S);
      if (it == 7) tile_max(b0, b1);
      expo(PA, LO);
      fence_regs(PA);
      sched_fence();
      finish_step(PB);
      finish_softmax(PA, it != 7);
    }
    bar_sync(NB_PP0 + w, 288);
    wg_fence(); issue_pv(PB, 1); wg_commit();
    if (w == 0) bar_arrive(NB_PP0 + 1, 288);
    row_norms(r0, r1);
    mbar_wait(bar(B_EMPTY + 1), 0);
    finish_step(PB);

    const uint32_t a_own = dK + ((w ? UNIT : OFF_STASH) >> 4), a_peer = dK + ((w ? 2 * UNIT : 4 * UNIT) >> 4);
    auto oproj_issue = [&](float (&acc)[64], int i) {
      const int buf = w_buf(i);
      mbar_wait(bar(B_WFULL + buf), w_phase(i));
      const uint32_t a = (w_peer(i) ? a_peer : a_own) + (i & 3) * 512, b = dN8 + (w_off(buf) >> 4);
      wg_fence();
#pragma unroll
      for (int kk = 0; kk < 4; kk++) wgmma_ss_n128<1>(acc, mk_desc(a + kk * 2), mk_desc(b + kk * 128), ((i & 7) | kk) != 0);
      wg_commit();
    };
    auto oproj_retire = [&](int i) {
      wg_wait<1>();
      if (leader) mbar_arrive(bar(B_WEMPTY + w_buf(i)));
    };
    store_tile(O, r0, r1, sb + UNIT + w * 16384 + tile_row, tile_sw);
    fence_async_smem();
    mbar_arrive(bar(B_O2_READY + w));
    if (w == 1) { mbar_wait(bar(B_O2_READY), 0); mbar_wait(bar(B_O2_READY + 1), 0); }
    oproj_issue(S, 0);
#pragma unroll 1
    for (int i = 1; i < 8; i++) {
      if (i == 4) mbar_wait(bar(w ? B_O2_IN : B_O1_IN), 0);
      if (i == 6 && w) mbar_wait(bar(B_O2_IN + 1), 0);
      oproj_issue(S, i);
      oproj_retire(i - 1);
    }
    if (leader) mbar_arrive_remote(mapa(bar(B_PEER_GOT), c ^ 1));
    oproj_issue(O, 8); oproj_retire(7);
    fence_regs(S);
    oproj_issue(O, 9); oproj_retire(8);
    const uint32_t stage1 = sb + (w ? 2 : 4) * UNIT + 16384;
    const uint32_t stage0 = stage1 - 16384 + tile_row;
    oproj_issue(O, 10); oproj_retire(9);
    oproj_issue(O, 11);
    store_tile(S, 1.f, 1.f, stage0, tile_sw);
    fence_async_smem();
    mbar_arrive(bar(B_STAGE_READY + w));
    mbar_wait(bar(B_ZERO_OK), 0);
    if (w == 1) bar_sync(NB_ORDER, 256);
#pragma unroll 1
    for (int i = 12; i < 16; i++) {
      wg_wait<1>();
      oproj_issue(O, i);
    }
    if (w == 0) bar_arrive(NB_ORDER, 256);
    wg_wait<0>();
    fence_regs(O);
    store_tile(O, 1.f, 1.f, stage1 + tile_row, tile_sw);
    fence_async_smem();
    bar_sync(NB_WG0 + w, 128);
    if (leader) {
      tma_red_3d(&p.out, (2 * bp + w) * 64, r * 8 + c * 4 + 2, stage1);
      asm volatile("cp.async.bulk.commit_group;" ::: "memory");
      asm volatile("cp.async.bulk.wait_group.read 0;" ::: "memory");
    }
    __syncwarp();
  }
}

typedef CUresult (*EncodeFn)(CUtensorMap*, CUtensorMapDataType, cuuint32_t, void*, const cuuint64_t*, const cuuint64_t*,
                             const cuuint32_t*, const cuuint32_t*, CUtensorMapInterleave, CUtensorMapSwizzle,
                             CUtensorMapL2promotion, CUtensorMapFloatOOBfill);

void encode_3d(EncodeFn fn, CUtensorMap* m, const void* ptr, uint64_t rows, uint64_t cols, uint32_t box_rows, uint32_t groups) {
  cuuint64_t dims[3] = {64, rows, cols / 64};
  cuuint64_t strides[2] = {cols * 2, 128};
  cuuint32_t box[3] = {64, box_rows, groups};
  cuuint32_t es[3] = {1, 1, 1};
  fn(m, CU_TENSOR_MAP_DATA_TYPE_BFLOAT16, 3, const_cast<void*>(ptr), dims, strides, box, es, CU_TENSOR_MAP_INTERLEAVE_NONE,
     CU_TENSOR_MAP_SWIZZLE_128B, CU_TENSOR_MAP_L2_PROMOTION_L2_128B, CU_TENSOR_MAP_FLOAT_OOB_FILL_NONE);
}
void encode_2d(EncodeFn fn, CUtensorMap* m, const void* ptr, uint64_t rows, uint64_t cols, uint32_t box_rows) {
  cuuint64_t dims[2] = {cols, rows};
  cuuint64_t strides[1] = {cols * 2};
  cuuint32_t box[2] = {64, box_rows};
  cuuint32_t es[2] = {1, 1};
  fn(m, CU_TENSOR_MAP_DATA_TYPE_BFLOAT16, 2, const_cast<void*>(ptr), dims, strides, box, es, CU_TENSOR_MAP_INTERLEAVE_NONE,
     CU_TENSOR_MAP_SWIZZLE_128B, CU_TENSOR_MAP_L2_PROMOTION_L2_128B, CU_TENSOR_MAP_FLOAT_OOB_FILL_NONE);
}

}

extern "C" void kernel_launch(void* const* d_in, const int* in_sizes, int n_in, void* d_out, int out_size) {
  (void)in_sizes; (void)n_in; (void)out_size;
  static EncodeFn encode = nullptr;
  if (!encode) {
    void* fn = nullptr;
    cudaDriverEntryPointQueryResult q;
    cudaGetDriverEntryPoint("cuTensorMapEncodeTiled", &fn, cudaEnableDefault, &q);
    encode = (EncodeFn)fn;
    cudaFuncSetAttribute(gqa_fused_kernel, cudaFuncAttributeMaxDynamicSharedMemorySize, SMEM_BYTES);
  }
  Params p;
  for (int r = 0; r < 2; r++) {
    void* const* in = d_in + 5 * r;
    encode_2d(encode, &p.x[r], in[0], 512, 512, 128);
    encode_3d(encode, &p.k[r], in[1], 131072, 128, 128, 2);
    encode_3d(encode, &p.v[r], in[2], 131072, 128, 128, 2);
    encode_3d(encode, &p.wq[r], in[3], 512, 4096, 64, 4);
    encode_3d(encode, &p.wo[r], in[4], 4096, 512, 64, 2);
  }
  for (int r = 0; r < 2; r++) {
    p.x_ptr[r] = (const char*)d_in[5 * r];
    p.wq_ptr[r] = (const char*)d_in[5 * r + 3];
    p.kv_ptr[r][0] = (const char*)d_in[5 * r + 1];
    p.kv_ptr[r][1] = (const char*)d_in[5 * r + 2];
  }
  encode_3d(encode, &p.out, d_out, 512, 1024, 64, 2);
  gqa_fused_kernel<<<128, 384, SMEM_BYTES, cudaStreamPerThread>>>(p, (__nv_bfloat16*)d_out);
}
```
